```python
import torch

def _softmax(x, axis=-1):
    return torch.softmax(x, dim=axis)
def _gelu(x):
    return torch.nn.functional.gelu(x, approximate="tanh")
def _silu(x):
    return torch.nn.functional.silu(x)
def _sigmoid(x):
    return torch.sigmoid(x)
def _layernorm(x, axis=-1, eps=1e-5):
    m = x.mean(dim=axis, keepdim=True)
    v = x.var(dim=axis, keepdim=True, unbiased=False)
    return (x - m) / torch.sqrt(v + eps)
def _scatter_add(tgt, idx, src, axis=0):
    return tgt.clone().index_add_(axis, idx, src)
def _segment_sum(src, seg, n):
    out = torch.zeros((n,) + src.shape[1:], dtype=src.dtype)
    return out.index_add_(0, seg, src)
def _pad(x, pw):
    flat = tuple(v for pair in reversed(pw) for v in pair)
    return torch.nn.functional.pad(x, flat)

kernel_name = 'standalone__low_rank_proj_linformer__decode'

def setup_inputs():

    _w = (lambda a: (lambda t: t.to(torch.bfloat16) if t.is_floating_point() else t)(torch.as_tensor(a)))
    B, H, Sq, Skv, Dh, R = 2, 32, 1, 16384, 128, 16
    return {
        "q": _w((lambda *s: torch.randn(*s, dtype=torch.bfloat16) * 0.8)(B, H, Sq, Dh)),
        "k": _w((lambda *s: torch.randn(*s, dtype=torch.bfloat16) * 0.8)(B, H, Skv, Dh)),
        "v": _w((lambda *s: torch.randn(*s, dtype=torch.bfloat16) * 0.05)(B, H, Skv, Dh)),
        "e_proj": _w((lambda *s: torch.randn(*s, dtype=torch.bfloat16) * 0.8)(R, Skv) * (Skv ** -0.5)),
        "f_proj": _w((lambda *s: torch.randn(*s, dtype=torch.bfloat16) * 0.05)(R, Skv) * (Skv ** -0.5)),
    }

def reference(q, k, v, e_proj, f_proj):
    B, H, Sq, Dh = q.shape
    kp = torch.einsum("rn,bhnd->bhrd", e_proj, k)
    vp = torch.einsum("rn,bhnd->bhrd", f_proj, v)
    scores = torch.einsum("bhqd,bhrd->bhqr", q, kp) * (Dh ** -0.5)
    p = _softmax(scores, axis=-1)
    o = torch.einsum("bhqr,bhrd->bhqd", p, vp)
    return o
```

```cpp
#include <cuda_runtime.h>
#include <cuda_bf16.h>
#include <cuda.h>
#include <stdint.h>

#define TR 256
#define NST 5
#define PR 128
#define PFMAP 1
#define PFENCE 0
#define FSEP 0

namespace {

constexpr int SKV = 16384, DH = 128, RK = 16, NHEADS = 64;
constexpr int TPM = SKV / TR;
constexpr int NT = 2 * TPM;
constexpr int KV_BYTES = TR * 128;
constexpr int E_BYTES = TR * RK * 2;
constexpr int SMEM_BYTES = NST * (KV_BYTES + E_BYTES) + 1024;
constexpr int PPT = TR / PR;
constexpr int NP = NST * PPT;
constexpr int NTHREADS = 160;
constexpr int SPIN_LIMIT = 1 << 22;
static_assert(NP + (FSEP ? NST : 0) <= 32, "one lane per polled barrier");
static_assert(PR % 64 == 0, "pieces cover whole 64-column E blocks");

__device__ __forceinline__ uint32_t smem_u32(const void* p) { return (uint32_t)__cvta_generic_to_shared(p); }
__device__ __forceinline__ void mbar_init(uint32_t bar, uint32_t cnt) {
    asm volatile("mbarrier.init.shared::cta.b64 [%0], %1;" ::"r"(bar), "r"(cnt) : "memory");
}
__device__ __forceinline__ void mbar_expect_tx(uint32_t bar, uint32_t bytes) {
    asm volatile("mbarrier.arrive.expect_tx.shared::cta.b64 _, [%0], %1;" ::"r"(bar), "r"(bytes) : "memory");
}
__device__ __forceinline__ void mbar_arrive(uint32_t bar) {
    asm volatile("mbarrier.arrive.shared::cta.b64 _, [%0];" ::"r"(bar) : "memory");
}
__device__ __forceinline__ void mbar_arrive_remote(uint32_t bar_cluster_addr) {
    asm volatile("mbarrier.arrive.shared::cluster.b64 _, [%0];" ::"r"(bar_cluster_addr) : "memory");
}
__device__ __forceinline__ uint32_t mbar_test(uint32_t bar, uint32_t parity) {
    uint32_t done;
    asm volatile("{ .reg .pred p; mbarrier.test_wait.parity.shared::cta.b64 p, [%1], %2; selp.u32 %0, 1, 0, p; }"
                 : "=r"(done) : "r"(bar), "r"(parity) : "memory");
    return done;
}
__device__ __forceinline__ void mbar_wait(uint32_t bar, uint32_t parity) {
    uint32_t done = 0;
#pragma unroll 1
    for (int it = 0; it < SPIN_LIMIT; it++) {
        asm volatile("{ .reg .pred p; mbarrier.try_wait.parity.shared::cta.b64 p, [%1], %2; selp.u32 %0, 1, 0, p; }"
                     : "=r"(done) : "r"(bar), "r"(parity) : "memory");
        if (done) return;
    }
    __trap();
}
__device__ __forceinline__ void mbar_wait_cluster(uint32_t bar, uint32_t parity) {
    uint32_t done = 0;
#pragma unroll 1
    for (int it = 0; it < SPIN_LIMIT; it++) {
        asm volatile("{ .reg .pred p; mbarrier.try_wait.parity.acquire.cluster.shared::cta.b64 p, [%1], %2; selp.u32 %0, 1, 0, p; }"
                     : "=r"(done) : "r"(bar), "r"(parity) : "memory");
        if (done) return;
    }
    __trap();
}
__device__ __forceinline__ uint32_t mapa(uint32_t addr, uint32_t rank) {
    uint32_t r;
    asm("mapa.shared::cluster.u32 %0, %1, %2;" : "=r"(r) : "r"(addr), "r"(rank));
    return r;
}
__device__ __forceinline__ void tma2d(uint32_t dst, const CUtensorMap* m, uint32_t bar, int c0, int c1, uint64_t pol) {
    asm volatile("cp.async.bulk.tensor.2d.shared::cluster.global.mbarrier::complete_tx::bytes.L2::cache_hint [%0], [%1, {%3, %4}], [%2], %5;"
                 ::"r"(dst), "l"(m), "r"(bar), "r"(c0), "r"(c1), "l"(pol) : "memory");
}
__device__ __forceinline__ void tma3d(uint32_t dst, const CUtensorMap* m, uint32_t bar, int c0, int c1, int c2) {
    asm volatile("cp.async.bulk.tensor.3d.shared::cluster.global.mbarrier::complete_tx::bytes [%0], [%1, {%3, %4, %5}], [%2];"
                 ::"r"(dst), "l"(m), "r"(bar), "r"(c0), "r"(c1), "r"(c2) : "memory");
}
__device__ __forceinline__ void prefetch_map(const CUtensorMap* m) {
    asm volatile("prefetch.tensormap [%0];" ::"l"(m) : "memory");
}
__device__ __forceinline__ uint64_t make_desc(uint32_t addr) {
    return (uint64_t)((addr & 0x3FFFF) >> 4) | (1ull << 16) | (64ull << 32) | (1ull << 62);
}
__device__ __forceinline__ void wgmma_m64n16k16(float (&d)[8], uint64_t da, uint64_t db, int scale_d) {
    asm volatile("{ .reg .pred p; setp.ne.b32 p, %10, 0;\n"
                 "wgmma.mma_async.sync.aligned.m64n16k16.f32.bf16.bf16 {%0,%1,%2,%3,%4,%5,%6,%7}, %8, %9, p, 1, 1, 1, 0; }"
                 : "+f"(d[0]), "+f"(d[1]), "+f"(d[2]), "+f"(d[3]), "+f"(d[4]), "+f"(d[5]), "+f"(d[6]), "+f"(d[7])
                 : "l"(da), "l"(db), "r"(scale_d));
}
__device__ __forceinline__ void wgmma_fence() { asm volatile("wgmma.fence.sync.aligned;" ::: "memory"); }
__device__ __forceinline__ void wgmma_commit() { asm volatile("wgmma.commit_group.sync.aligned;" ::: "memory"); }
__device__ __forceinline__ void wgmma_wait0() { asm volatile("wgmma.wait_group.sync.aligned 0;" ::: "memory"); }
__device__ __forceinline__ void reg_fence(float (&d)[8]) {
    asm volatile("" : "+f"(d[0]), "+f"(d[1]), "+f"(d[2]), "+f"(d[3]), "+f"(d[4]), "+f"(d[5]), "+f"(d[6]), "+f"(d[7])::"memory");
}
__device__ __forceinline__ float rbf(float x) { return __bfloat162float(__float2bfloat16_rn(x)); }
__device__ __forceinline__ void rbf2(float a, float b, float& ra, float& rb) {
    uint32_t u;
    asm("cvt.rn.bf16x2.f32 %0, %1, %2;" : "=r"(u) : "f"(b), "f"(a));
    ra = __uint_as_float(u << 16);
    rb = __uint_as_float(u & 0xffff0000u);
}

__global__ void __cluster_dims__(2, 1, 1) __launch_bounds__(NTHREADS, 1)
linformer_decode_kernel(const __grid_constant__ CUtensorMap mK, const __grid_constant__ CUtensorMap mV,
                        const __grid_constant__ CUtensorMap mE, const __grid_constant__ CUtensorMap mF,
                        const __grid_constant__ CUtensorMap mVp, const __grid_constant__ CUtensorMap mFp,
                        const __nv_bfloat16* __restrict__ q, __nv_bfloat16* __restrict__ out) {
    extern __shared__ unsigned char smem_raw[];
    __shared__ __align__(8) unsigned long long full_bar[NST], empty_bar[NST], piece_bar[NP], score_bar;
    __shared__ volatile uint32_t ready_slot[2];
    __shared__ float score_part[8][RK];

    const int tid = threadIdx.x, warp = __shfl_sync(0xffffffffu, tid >> 5, 0), lane = tid & 31;
    const int head = blockIdx.x >> 1, half = blockIdx.x & 1;
    const uint32_t kvbase = (smem_u32(smem_raw) + 1023) & ~1023u;
    const uint32_t ebase = kvbase + NST * KV_BYTES;

    if (warp == 4) {
        uint64_t pol;
        asm volatile("createpolicy.fractional.L2::evict_first.b64 %0, 1.0;" : "=l"(pol));
        if (lane == 0) {
#pragma unroll
            for (int s = 0; s < NST; s++) {
                const uint32_t bar = smem_u32(&full_bar[s]);
                mbar_init(bar, 1);
                if (PFENCE) asm volatile("fence.proxy.async.shared::cta;" ::: "memory");
                mbar_expect_tx(bar, KV_BYTES + E_BYTES);
                tma2d(kvbase + s * KV_BYTES, &mK, bar, half * 64, head * SKV + s * TR, pol);
                tma3d(ebase + s * E_BYTES, &mE, bar, 0, 0, s * (TR / 64));
            }
#pragma unroll
            for (int s = 0; s < NST; s++) mbar_init(smem_u32(&empty_bar[s]), 4);
#pragma unroll
            for (int s = 0; s < NP; s++) mbar_init(smem_u32(&piece_bar[s]), 1);
            mbar_init(smem_u32(&score_bar), 32);
            asm volatile("fence.mbarrier_init.release.cluster;" ::: "memory");
        }
        __syncwarp();
        asm volatile("bar.arrive 1, 160;" ::: "memory");
        asm volatile("barrier.cluster.arrive.relaxed.aligned;" ::: "memory");
        if (lane == 0) {
            int s = 0, ph = 0;
#pragma unroll 1
            for (int i = NST; i < NT; i++) {
                const bool isV = i >= TPM;
                const int j = isV ? i - TPM : i;
                const uint32_t bar = smem_u32(&full_bar[s]);
                mbar_wait(smem_u32(&empty_bar[s]), ph);
                if (i < NT - NST) {
                    mbar_expect_tx(bar, KV_BYTES + E_BYTES);
                    tma2d(kvbase + s * KV_BYTES, isV ? &mV : &mK, bar, half * 64, head * SKV + j * TR, pol);
                    tma3d(ebase + s * E_BYTES, isV ? &mF : &mE, bar, 0, 0, j * (TR / 64));
                } else {
                    if (FSEP) {
                        mbar_expect_tx(bar, E_BYTES);
                        tma3d(ebase + s * E_BYTES, &mF, bar, 0, 0, j * (TR / 64));
                    }
#pragma unroll
                    for (int u = 0; u < PPT; u++) {
                        const int pc = s * PPT + u;
                        const uint32_t pb = smem_u32(&piece_bar[pc]);
                        mbar_expect_tx(pb, PR * 128 + (FSEP ? 0 : PR * 32));
                        tma2d(kvbase + pc * (PR * 128), &mVp, pb, half * 64, head * SKV + j * TR + u * PR, pol);
                        if (!FSEP) tma3d(ebase + pc * (PR * 32), &mFp, pb, 0, 0, j * (TR / 64) + u * (PR / 64));
                    }
                }
                if (++s == NST) { s = 0; ph ^= 1; }
            }
        }
        __syncwarp();
        asm volatile("barrier.cluster.wait.aligned;" ::: "memory");
    } else {
        if (PFMAP && tid == 0) { prefetch_map(&mK); prefetch_map(&mE); }
        asm volatile("barrier.cluster.arrive.relaxed.aligned;" ::: "memory");
        const int g = lane >> 2, t = lane & 3;
        const int row0 = warp * 16 + g;
        const float q0 = __bfloat162float(q[head * DH + half * 64 + row0]);
        const float q1 = __bfloat162float(q[head * DH + half * 64 + row0 + 8]);
        __nv_bfloat16* optr = out + head * DH + half * 64 + row0 + 8 * (t & 1);
        asm volatile("" : "+l"(optr));
        asm volatile("bar.sync 1, 160;" ::: "memory");

        const uint64_t da0 = make_desc(kvbase), db0 = make_desc(ebase);
        float acc[8];
        float p[4];
        int s = 0, ph = 0;
#pragma unroll 1
        for (int i = 0; i < NT - NST; i++) {
            if (i == TPM + TPM / 2) {
                mbar_wait_cluster(smem_u32(&score_bar), 0);
                const int r = lane & 15;
                float sc = 0.f;
#pragma unroll
                for (int w = 0; w < 8; w++) sc += score_part[w][r];
                sc = rbf(rbf(sc) * 0.08838834764831845f);
                float mx = sc;
#pragma unroll
                for (int o = 8; o >= 1; o >>= 1) mx = fmaxf(mx, __shfl_xor_sync(0xffffffffu, mx, o));
                const float ex = expf(sc - mx);
                float sum = ex;
#pragma unroll
                for (int o = 8; o >= 1; o >>= 1) sum += __shfl_xor_sync(0xffffffffu, sum, o);
                const float pr = rbf(ex / sum);
                p[0] = __shfl_sync(0xffffffffu, pr, 2 * t);
                p[1] = __shfl_sync(0xffffffffu, pr, 2 * t + 1);
                p[2] = __shfl_sync(0xffffffffu, pr, 8 + 2 * t);
                p[3] = __shfl_sync(0xffffffffu, pr, 9 + 2 * t);
                if (PFMAP && tid == 0) { prefetch_map(&mVp); prefetch_map(&mFp); }
            }
            mbar_wait(smem_u32(&full_bar[s]), ph);
            const uint64_t da = da0 + s * (KV_BYTES >> 4), db = db0 + s * (E_BYTES >> 4);
            const int first = (i == 0 || i == TPM) ? 0 : 1;
            reg_fence(acc);
            wgmma_fence();
#pragma unroll
            for (int k = 0; k < TR / 16; k++)
                wgmma_m64n16k16(acc, da + k * (2048 >> 4), db + (k >> 2) * (2048 >> 4) + (k & 3) * (32 >> 4), k == 0 ? first : 1);
            wgmma_commit();
            wgmma_wait0();
            reg_fence(acc);
            if (lane == 0) mbar_arrive(smem_u32(&empty_bar[s]));
            if (i == TPM - 1) {
                float sp[4];
                sp[0] = q0 * rbf(acc[0]) + q1 * rbf(acc[2]);
                sp[1] = q0 * rbf(acc[1]) + q1 * rbf(acc[3]);
                sp[2] = q0 * rbf(acc[4]) + q1 * rbf(acc[6]);
                sp[3] = q0 * rbf(acc[5]) + q1 * rbf(acc[7]);
#pragma unroll
                for (int o = 4; o <= 16; o <<= 1)
#pragma unroll
                    for (int c = 0; c < 4; c++) sp[c] += __shfl_xor_sync(0xffffffffu, sp[c], o);
                asm volatile("barrier.cluster.wait.aligned;" ::: "memory");
                if (lane < 4) {
                    const uint32_t a = smem_u32(&score_part[half * 4 + warp][2 * t]);
#pragma unroll
                    for (int rk = 0; rk < 2; rk++) {
                        const uint32_t ra = mapa(a, rk);
                        asm volatile("st.shared::cluster.v2.f32 [%0], {%1, %2};" ::"r"(ra), "f"(sp[0]), "f"(sp[1]) : "memory");
                        asm volatile("st.shared::cluster.v2.f32 [%0], {%1, %2};" ::"r"(ra + 32), "f"(sp[2]), "f"(sp[3]) : "memory");
                    }
                    asm volatile("fence.acq_rel.cluster;" ::: "memory");
#pragma unroll
                    for (int rk = 0; rk < 2; rk++) mbar_arrive_remote(mapa(smem_u32(&score_bar), rk));
                }
            }
            if (PFMAP && i == TPM - 2 * NST && tid == 0) { prefetch_map(&mV); prefetch_map(&mF); }
            if (++s == NST) { s = 0; ph ^= 1; }
        }

        {
            const int fs = min(max(lane - NP, 0), NST - 1);
            const int fi = NT - NST + (fs + NST - (NT - NST) % NST) % NST;
            const uint32_t my_bar = lane < NP ? smem_u32(&piece_bar[lane]) : smem_u32(&full_bar[fs]);
            const uint32_t my_par = lane < NP ? 0 : (fi / NST) & 1;
            uint32_t pending = (NP == 32) ? 0xffffffffu : ((1u << NP) - 1);
            int round = 0;
            reg_fence(acc);
#pragma unroll 1
            do {
                if (warp == 0) {
                    uint32_t rdy;
                    int spins = 0;
                    const bool want = lane < NP ? ((pending >> lane) & 1) : (FSEP && lane < NP + NST);
#pragma unroll 1
                    while (true) {
                        rdy = __ballot_sync(0xffffffffu, want && mbar_test(my_bar, my_par));
                        if (FSEP) {
                            uint32_t fm = 0;
#pragma unroll
                            for (int f = 0; f < NST; f++)
                                if ((rdy >> (NP + f)) & 1) fm |= ((1u << PPT) - 1) << (f * PPT);
                            rdy &= fm;
                        }
                        if (rdy) break;
                        if (++spins > SPIN_LIMIT) __trap();
                    }
                    __syncwarp();
                    if (lane == 0) ready_slot[round & 1] = rdy;
                }
                asm volatile("bar.sync 2, 128;" ::: "memory");
                uint32_t ready;
                ready = __shfl_sync(0xffffffffu, ready_slot[round & 1], 0);
                round++;
                pending &= ~ready;
#pragma unroll 1
                do {
                    const uint32_t pc = __ffs(ready) - 1;
                    ready &= ready - 1;
                    const uint64_t da = da0 + pc * (PR * 128 >> 4), db = db0 + pc * (PR * 32 >> 4);
                    wgmma_fence();
#pragma unroll
                    for (int k = 0; k < PR / 16; k++)
                        wgmma_m64n16k16(acc, da + k * (2048 >> 4), db + (k >> 2) * (2048 >> 4) + (k & 3) * (32 >> 4), 1);
                    wgmma_commit();
                } while (ready);
            } while (pending);
            wgmma_wait0();
            reg_fence(acc);
        }
        float x[8];
#pragma unroll
        for (int c = 0; c < 8; c += 2) rbf2(acc[c], acc[c + 1], x[c], x[c + 1]);
        const float o0 = (p[0] * x[0] + p[1] * x[1]) + (p[2] * x[4] + p[3] * x[5]);
        const float o1 = (p[0] * x[2] + p[1] * x[3]) + (p[2] * x[6] + p[3] * x[7]);
        float keep = (t & 1) ? o1 : o0;
        keep += __shfl_xor_sync(0xffffffffu, (t & 1) ? o0 : o1, 1);
        keep += __shfl_xor_sync(0xffffffffu, keep, 2);
        if (t < 2) *optr = __float2bfloat16_rn(keep);
    }
}

typedef CUresult (*EncodeTiledFn)(CUtensorMap*, CUtensorMapDataType, cuuint32_t, void*, const cuuint64_t*, const cuuint64_t*,
                                  const cuuint32_t*, const cuuint32_t*, CUtensorMapInterleave, CUtensorMapSwizzle,
                                  CUtensorMapL2promotion, CUtensorMapFloatOOBfill);

void encode_kv(EncodeTiledFn enc, CUtensorMap* m, void* p, int rows) {
    cuuint64_t dims[2] = {(cuuint64_t)DH, (cuuint64_t)NHEADS * SKV};
    cuuint64_t str[1] = {DH * 2};
    cuuint32_t box[2] = {64, (cuuint32_t)rows};
    cuuint32_t es[2] = {1, 1};
    enc(m, CU_TENSOR_MAP_DATA_TYPE_BFLOAT16, 2, p, dims, str, box, es, CU_TENSOR_MAP_INTERLEAVE_NONE,
        CU_TENSOR_MAP_SWIZZLE_128B, CU_TENSOR_MAP_L2_PROMOTION_NONE, CU_TENSOR_MAP_FLOAT_OOB_FILL_NONE);
}
void encode_ef(EncodeTiledFn enc, CUtensorMap* m, void* p, int rows) {
    cuuint64_t dims[3] = {64, (cuuint64_t)RK, (cuuint64_t)SKV / 64};
    cuuint64_t str[2] = {SKV * 2, 128};
    cuuint32_t box[3] = {64, RK, (cuuint32_t)rows / 64};
    cuuint32_t es[3] = {1, 1, 1};
    enc(m, CU_TENSOR_MAP_DATA_TYPE_BFLOAT16, 3, p, dims, str, box, es, CU_TENSOR_MAP_INTERLEAVE_NONE,
        CU_TENSOR_MAP_SWIZZLE_128B, CU_TENSOR_MAP_L2_PROMOTION_NONE, CU_TENSOR_MAP_FLOAT_OOB_FILL_NONE);
}

}

extern "C" void kernel_launch(void* const* d_in, const int* in_sizes, int n_in, void* d_out, int out_size) {
    (void)in_sizes; (void)n_in; (void)out_size;
    static EncodeTiledFn enc = nullptr;
    if (!enc) {
        cudaDriverEntryPointQueryResult qr;
        cudaGetDriverEntryPoint("cuTensorMapEncodeTiled", (void**)&enc, cudaEnableDefault, &qr);
        cudaFuncSetAttribute(linformer_decode_kernel, cudaFuncAttributeMaxDynamicSharedMemorySize, SMEM_BYTES);
    }
    CUtensorMap mK, mV, mVp, mE, mF, mFp;
    encode_kv(enc, &mK, d_in[1], TR);
    encode_kv(enc, &mV, d_in[2], TR);
    encode_kv(enc, &mVp, d_in[2], PR);
    encode_ef(enc, &mE, d_in[3], TR);
    encode_ef(enc, &mF, d_in[4], TR);
    encode_ef(enc, &mFp, d_in[4], PR);
    linformer_decode_kernel<<<2 * NHEADS, NTHREADS, SMEM_BYTES, cudaStreamPerThread>>>(
        mK, mV, mE, mF, mVp, mFp, (const __nv_bfloat16*)d_in[0], (__nv_bfloat16*)d_out);
}
```

```cpp
#include <cuda_runtime.h>
#include <cuda_bf16.h>
#include <cuda.h>
#include <stdint.h>

#define TR 128
#define NST 8
#define LEAD8 16
#define MAXW 900

namespace {

constexpr int SKV = 16384, DH = 128, RK = 16, NHEADS = 64;
constexpr int TPM = SKV / TR;
constexpr int NT = 2 * TPM;
constexpr int KV_BYTES = TR * 128;
constexpr int E_BYTES = TR * RK * 2;
constexpr int SMEM_BYTES = NST * (KV_BYTES + E_BYTES) + 1024;
constexpr int NTHREADS = 192;
constexpr int SPIN_LIMIT = 1 << 24;
constexpr uint32_t PROG_WRAP = NHEADS * (NT - NST) - 1;

__device__ __forceinline__ uint32_t smem_u32(const void* p) { return (uint32_t)__cvta_generic_to_shared(p); }
__device__ __forceinline__ void mbar_init(uint32_t bar, uint32_t cnt) {
    asm volatile("mbarrier.init.shared::cta.b64 [%0], %1;" ::"r"(bar), "r"(cnt) : "memory");
}
__device__ __forceinline__ void mbar_expect_tx(uint32_t bar, uint32_t bytes) {
    asm volatile("mbarrier.arrive.expect_tx.shared::cta.b64 _, [%0], %1;" ::"r"(bar), "r"(bytes) : "memory");
}
__device__ __forceinline__ void mbar_arrive(uint32_t bar) {
    asm volatile("mbarrier.arrive.shared::cta.b64 _, [%0];" ::"r"(bar) : "memory");
}
__device__ __forceinline__ void mbar_arrive_remote(uint32_t bar_cluster_addr) {
    asm volatile("mbarrier.arrive.shared::cluster.b64 _, [%0];" ::"r"(bar_cluster_addr) : "memory");
}
__device__ __forceinline__ void mbar_wait(uint32_t bar, uint32_t parity) {
    uint32_t done = 0;
#pragma unroll 1
    for (int it = 0; it < SPIN_LIMIT; it++) {
        asm volatile("{ .reg .pred p; mbarrier.try_wait.parity.shared::cta.b64 p, [%1], %2; selp.u32 %0, 1, 0, p; }"
                     : "=r"(done) : "r"(bar), "r"(parity) : "memory");
        if (done) return;
    }
    __trap();
}
__device__ __forceinline__ void mbar_wait_cluster(uint32_t bar, uint32_t parity) {
    uint32_t done = 0;
#pragma unroll 1
    for (int it = 0; it < SPIN_LIMIT; it++) {
        asm volatile("{ .reg .pred p; mbarrier.try_wait.parity.acquire.cluster.shared::cta.b64 p, [%1], %2; selp.u32 %0, 1, 0, p; }"
                     : "=r"(done) : "r"(bar), "r"(parity) : "memory");
        if (done) return;
    }
    __trap();
}
__device__ __forceinline__ uint32_t mapa(uint32_t addr, uint32_t rank) {
    uint32_t r;
    asm("mapa.shared::cluster.u32 %0, %1, %2;" : "=r"(r) : "r"(addr), "r"(rank));
    return r;
}
__device__ __forceinline__ void tma2d(uint32_t dst, const CUtensorMap* m, uint32_t bar, int c0, int c1, uint64_t pol) {
    asm volatile("cp.async.bulk.tensor.2d.shared::cluster.global.mbarrier::complete_tx::bytes.L2::cache_hint [%0], [%1, {%3, %4}], [%2], %5;"
                 ::"r"(dst), "l"(m), "r"(bar), "r"(c0), "r"(c1), "l"(pol) : "memory");
}
__device__ __forceinline__ void tma3d(uint32_t dst, const CUtensorMap* m, uint32_t bar, int c0, int c1, int c2) {
    asm volatile("cp.async.bulk.tensor.3d.shared::cluster.global.mbarrier::complete_tx::bytes [%0], [%1, {%3, %4, %5}], [%2];"
                 ::"r"(dst), "l"(m), "r"(bar), "r"(c0), "r"(c1), "r"(c2) : "memory");
}
__device__ __forceinline__ uint64_t make_desc(uint32_t addr) {
    return (uint64_t)((addr & 0x3FFFF) >> 4) | (1ull << 16) | (64ull << 32) | (1ull << 62);
}
__device__ __forceinline__ void wgmma_m64n16k16(float (&d)[8], uint64_t da, uint64_t db, int scale_d) {
    asm volatile("{ .reg .pred p; setp.ne.b32 p, %10, 0;\n"
                 "wgmma.mma_async.sync.aligned.m64n16k16.f32.bf16.bf16 {%0,%1,%2,%3,%4,%5,%6,%7}, %8, %9, p, 1, 1, 1, 0; }"
                 : "+f"(d[0]), "+f"(d[1]), "+f"(d[2]), "+f"(d[3]), "+f"(d[4]), "+f"(d[5]), "+f"(d[6]), "+f"(d[7])
                 : "l"(da), "l"(db), "r"(scale_d));
}
__device__ __forceinline__ void wgmma_fence() { asm volatile("wgmma.fence.sync.aligned;" ::: "memory"); }
__device__ __forceinline__ void wgmma_commit() { asm volatile("wgmma.commit_group.sync.aligned;" ::: "memory"); }
__device__ __forceinline__ void wgmma_wait0() { asm volatile("wgmma.wait_group.sync.aligned 0;" ::: "memory"); }
__device__ __forceinline__ void reg_fence(float (&d)[8]) {
    asm volatile("" : "+f"(d[0]), "+f"(d[1]), "+f"(d[2]), "+f"(d[3]), "+f"(d[4]), "+f"(d[5]), "+f"(d[6]), "+f"(d[7])::"memory");
}
__device__ __forceinline__ float rbf(float x) { return __bfloat162float(__float2bfloat16_rn(x)); }
__device__ __forceinline__ void rbf2(float a, float b, float& ra, float& rb) {
    uint32_t u;
    asm("cvt.rn.bf16x2.f32 %0, %1, %2;" : "=r"(u) : "f"(b), "f"(a));
    ra = __uint_as_float(u << 16);
    rb = __uint_as_float(u & 0xffff0000u);
}

__device__ unsigned int g_prog;
__device__ __forceinline__ void prog_inc() {
    asm volatile("red.relaxed.gpu.global.inc.u32 [%0], %1;" ::"l"(&g_prog), "r"(PROG_WRAP) : "memory");
}

__global__ void __cluster_dims__(2, 1, 1) __launch_bounds__(NTHREADS, 1)
linformer_decode_kernel(const __grid_constant__ CUtensorMap mK, const __grid_constant__ CUtensorMap mV,
                        const __grid_constant__ CUtensorMap mE, const __grid_constant__ CUtensorMap mF,
                        const __nv_bfloat16* __restrict__ q, __nv_bfloat16* __restrict__ out) {
    extern __shared__ unsigned char smem_raw[];
    __shared__ __align__(8) unsigned long long full_bar[NST], empty_bar[NST], score_bar, pace_bar;
    __shared__ __align__(16) float score_part[8][RK];
    __shared__ volatile int s_issued, s_limit;

    const int tid = threadIdx.x;
    const int head = blockIdx.x >> 1, half = blockIdx.x & 1;
    const uint32_t kvbase = (smem_u32(smem_raw) + 1023) & ~1023u;
    const uint32_t ebase = kvbase + NST * KV_BYTES;

    uint64_t pol;
    asm volatile("createpolicy.fractional.L2::evict_first.b64 %0, 1.0;" : "=l"(pol));
    if (tid == 128) {
#pragma unroll 1
        for (int s = 0; s < NST; s++) {
            const uint32_t bar = smem_u32(&full_bar[s]);
            mbar_init(bar, 1);
            mbar_expect_tx(bar, KV_BYTES + E_BYTES);
            tma2d(kvbase + s * KV_BYTES, &mK, bar, half * 64, head * SKV + s * TR, pol);
            tma3d(ebase + s * E_BYTES, &mE, bar, 0, 0, s * (TR / 64));
        }
    }
    if (tid == 0) {
#pragma unroll 1
        for (int s = 0; s < NST; s++) mbar_init(smem_u32(&empty_bar[s]), 4);
        mbar_init(smem_u32(&score_bar), 32);
        mbar_init(smem_u32(&pace_bar), 1);
        s_issued = NST;
        s_limit = NST + LEAD8 / 8;
        asm volatile("fence.mbarrier_init.release.cluster;" ::: "memory");
    }
    __syncthreads();
    asm volatile("barrier.cluster.arrive.relaxed.aligned;" ::: "memory");

    const int warp = __shfl_sync(0xffffffffu, tid >> 5, 0), lane = tid & 31;
    if (warp == 4) {
        if (lane == 0) {
            int s = 0, ph = 0;
#pragma unroll 1
            for (int i = NST; i < NT; i++) {
                const bool isV = i >= TPM;
                const int j = isV ? i - TPM : i;
                const uint32_t bar = smem_u32(&full_bar[s]);
                mbar_wait(smem_u32(&empty_bar[s]), ph);
                if (i > s_limit) {
                    const long long t0 = clock64();
                    while (i > s_limit && clock64() - t0 < MAXW) {}
                }
                mbar_expect_tx(bar, KV_BYTES + E_BYTES);
                tma2d(kvbase + s * KV_BYTES, isV ? &mV : &mK, bar, half * 64, head * SKV + j * TR, pol);
                tma3d(ebase + s * E_BYTES, isV ? &mF : &mE, bar, 0, 0, j * (TR / 64));
                s_issued = i + 1;
                if (++s == NST) { s = 0; ph ^= 1; }
            }
        }
        __syncwarp();
        asm volatile("barrier.cluster.wait.aligned;" ::: "memory");
    } else if (warp == 5) {
        asm volatile("barrier.cluster.wait.aligned;" ::: "memory");
        if (lane == 0) {
            if (half == 0) {
                const uint32_t lim_peer = mapa(smem_u32((const void*)&s_limit), 1);
                const uint32_t bar_peer = mapa(smem_u32(&pace_bar), 1);
                int reported = NST, last = -1, sent = 0;
#pragma unroll 1
                for (int it = 0; it < SPIN_LIMIT; it++) {
                    const int cur = s_issued;
#pragma unroll 1
                    for (; reported < cur; reported++) prog_inc();
                    int lim = NT;
                    if (cur < NT - 1) {
                        unsigned int gsum;
                        asm volatile("ld.relaxed.gpu.global.u32 %0, [%1];" : "=r"(gsum) : "l"(&g_prog) : "memory");
                        lim = NST + (int)((gsum + LEAD8 * (NHEADS / 8)) / NHEADS);
                    }
                    if (lim != last) {
                        last = lim;
                        s_limit = lim;
                        asm volatile("st.async.shared::cluster.mbarrier::complete_tx::bytes.u32 [%0], %1, [%2];"
                                     ::"r"(lim_peer), "r"(lim), "r"(bar_peer) : "memory");
                        sent += 4;
                    }
                    if (cur == NT) break;
                }
                asm volatile("mbarrier.arrive.expect_tx.shared::cluster.b64 _, [%0], %1;" ::"r"(bar_peer), "r"(sent) : "memory");
            } else {
                mbar_wait(smem_u32(&pace_bar), 0);
            }
        }
    } else {
        const int g = lane >> 2, t = lane & 3;
        const int row0 = warp * 16 + g;
        uint32_t qraw0, qraw1;
        {
            const __nv_bfloat16* qp = q + head * DH + half * 64 + row0;
            asm volatile("ld.global.nc.u16 %0, [%1];" : "=r"(qraw0) : "l"(qp));
            asm volatile("ld.global.nc.u16 %0, [%1+16];" : "=r"(qraw1) : "l"(qp));
        }
        __nv_bfloat16* optr = out + head * DH + half * 64 + row0 + 8 * (t & 1);
        asm volatile("" : "+l"(optr));

        const uint64_t da0 = make_desc(kvbase), db0 = make_desc(ebase);
        float acc[8];
        float p[4];
        int s = 0, ph = 0;
#pragma unroll 1
        for (int i = 0; i < NT; i++) {
            if (i == TPM + TPM / 2) {
                mbar_wait_cluster(smem_u32(&score_bar), 0);
                const int r = lane & 15;
                float sc = 0.f;
#pragma unroll
                for (int w = 0; w < 8; w++) sc += score_part[w][r];
                sc = rbf(rbf(sc) * 0.08838834764831845f);
                float mx = sc;
#pragma unroll
                for (int o = 8; o >= 1; o >>= 1) mx = fmaxf(mx, __shfl_xor_sync(0xffffffffu, mx, o));
                const float ex = expf(sc - mx);
                float sum = ex;
#pragma unroll
                for (int o = 8; o >= 1; o >>= 1) sum += __shfl_xor_sync(0xffffffffu, sum, o);
                const float pr = rbf(ex / sum);
                p[0] = __shfl_sync(0xffffffffu, pr, 2 * t);
                p[1] = __shfl_sync(0xffffffffu, pr, 2 * t + 1);
                p[2] = __shfl_sync(0xffffffffu, pr, 8 + 2 * t);
                p[3] = __shfl_sync(0xffffffffu, pr, 9 + 2 * t);
            }
            mbar_wait(smem_u32(&full_bar[s]), ph);
            const uint64_t da = da0 + s * (KV_BYTES >> 4), db = db0 + s * (E_BYTES >> 4);
            const int first = (i == 0 || i == TPM) ? 0 : 1;
            reg_fence(acc);
            wgmma_fence();
#pragma unroll
            for (int k = 0; k < TR / 16; k++)
                wgmma_m64n16k16(acc, da + k * (2048 >> 4), db + (k >> 2) * (2048 >> 4) + (k & 3) * (32 >> 4), k == 0 ? first : 1);
            wgmma_commit();
            wgmma_wait0();
            reg_fence(acc);
            if (lane == 0) mbar_arrive(smem_u32(&empty_bar[s]));
            if (i == TPM - 1) {
                float sp[4], q0, q1;
                asm volatile("shl.b32 %0, %1, 16;" : "=f"(q0) : "r"(qraw0));
                asm volatile("shl.b32 %0, %1, 16;" : "=f"(q1) : "r"(qraw1));
                sp[0] = q0 * rbf(acc[0]) + q1 * rbf(acc[2]);
                sp[1] = q0 * rbf(acc[1]) + q1 * rbf(acc[3]);
                sp[2] = q0 * rbf(acc[4]) + q1 * rbf(acc[6]);
                sp[3] = q0 * rbf(acc[5]) + q1 * rbf(acc[7]);
#pragma unroll
                for (int o = 4; o <= 16; o <<= 1)
#pragma unroll
                    for (int c = 0; c < 4; c++) sp[c] += __shfl_xor_sync(0xffffffffu, sp[c], o);
                asm volatile("barrier.cluster.wait.aligned;" ::: "memory");
                if (lane < 4) {
                    const uint32_t a = smem_u32(&score_part[half * 4 + warp][2 * t]);
#pragma unroll
                    for (int rk = 0; rk < 2; rk++) {
                        const uint32_t ra = mapa(a, rk);
                        asm volatile("st.shared::cluster.v2.f32 [%0], {%1, %2};" ::"r"(ra), "f"(sp[0]), "f"(sp[1]) : "memory");
                        asm volatile("st.shared::cluster.v2.f32 [%0], {%1, %2};" ::"r"(ra + 32), "f"(sp[2]), "f"(sp[3]) : "memory");
                    }
                    asm volatile("fence.acq_rel.cluster;" ::: "memory");
#pragma unroll
                    for (int rk = 0; rk < 2; rk++) mbar_arrive_remote(mapa(smem_u32(&score_bar), rk));
                }
            }
            if (++s == NST) { s = 0; ph ^= 1; }
        }
        float x[8];
#pragma unroll
        for (int c = 0; c < 8; c += 2) rbf2(acc[c], acc[c + 1], x[c], x[c + 1]);
        const float o0 = (p[0] * x[0] + p[1] * x[1]) + (p[2] * x[4] + p[3] * x[5]);
        const float o1 = (p[0] * x[2] + p[1] * x[3]) + (p[2] * x[6] + p[3] * x[7]);
        float keep = (t & 1) ? o1 : o0;
        keep += __shfl_xor_sync(0xffffffffu, (t & 1) ? o0 : o1, 1);
        keep += __shfl_xor_sync(0xffffffffu, keep, 2);
        if (t < 2) *optr = __float2bfloat16_rn(keep);
    }
}

typedef CUresult (*EncodeTiledFn)(CUtensorMap*, CUtensorMapDataType, cuuint32_t, void*, const cuuint64_t*, const cuuint64_t*,
                                  const cuuint32_t*, const cuuint32_t*, CUtensorMapInterleave, CUtensorMapSwizzle,
                                  CUtensorMapL2promotion, CUtensorMapFloatOOBfill);

void encode_kv(EncodeTiledFn enc, CUtensorMap* m, void* p) {
    cuuint64_t dims[2] = {(cuuint64_t)DH, (cuuint64_t)NHEADS * SKV};
    cuuint64_t str[1] = {DH * 2};
    cuuint32_t box[2] = {64, TR};
    cuuint32_t es[2] = {1, 1};
    enc(m, CU_TENSOR_MAP_DATA_TYPE_BFLOAT16, 2, p, dims, str, box, es, CU_TENSOR_MAP_INTERLEAVE_NONE,
        CU_TENSOR_MAP_SWIZZLE_128B, CU_TENSOR_MAP_L2_PROMOTION_NONE, CU_TENSOR_MAP_FLOAT_OOB_FILL_NONE);
}
void encode_ef(EncodeTiledFn enc, CUtensorMap* m, void* p) {
    cuuint64_t dims[3] = {64, (cuuint64_t)RK, (cuuint64_t)SKV / 64};
    cuuint64_t str[2] = {SKV * 2, 128};
    cuuint32_t box[3] = {64, RK, TR / 64};
    cuuint32_t es[3] = {1, 1, 1};
    enc(m, CU_TENSOR_MAP_DATA_TYPE_BFLOAT16, 3, p, dims, str, box, es, CU_TENSOR_MAP_INTERLEAVE_NONE,
        CU_TENSOR_MAP_SWIZZLE_128B, CU_TENSOR_MAP_L2_PROMOTION_NONE, CU_TENSOR_MAP_FLOAT_OOB_FILL_NONE);
}

}

extern "C" void kernel_launch(void* const* d_in, const int* in_sizes, int n_in, void* d_out, int out_size) {
    (void)in_sizes; (void)n_in; (void)out_size;
    static EncodeTiledFn enc = nullptr;
    if (!enc) {
        cudaDriverEntryPointQueryResult qr;
        cudaGetDriverEntryPoint("cuTensorMapEncodeTiled", (void**)&enc, cudaEnableDefault, &qr);
        cudaFuncSetAttribute(linformer_decode_kernel, cudaFuncAttributeMaxDynamicSharedMemorySize, SMEM_BYTES);
    }
    CUtensorMap mK, mV, mE, mF;
    encode_kv(enc, &mK, d_in[1]);
    encode_kv(enc, &mV, d_in[2]);
    encode_ef(enc, &mE, d_in[3]);
    encode_ef(enc, &mF, d_in[4]);
    linformer_decode_kernel<<<2 * NHEADS, NTHREADS, SMEM_BYTES, cudaStreamPerThread>>>(
        mK, mV, mE, mF, (const __nv_bfloat16*)d_in[0], (__nv_bfloat16*)d_out);
}
```

```cpp
#include <cuda_runtime.h>
#include <cuda_bf16.h>
#include <cuda.h>
#include <stdint.h>

#define TR 128
#define NST 8
#define LEAD8 11
#define MAXW 900
#define EA 16

namespace {

constexpr int SKV = 16384, DH = 128, RK = 16, NHEADS = 64;
constexpr int TPM = SKV / TR;
constexpr int NT = 2 * TPM;
constexpr int KV_BYTES = TR * 128;
constexpr int E_BYTES = TR * RK * 2;
constexpr int SMEM_BYTES = NST * (KV_BYTES + E_BYTES) + 1024;
constexpr int NTHREADS = 192;
constexpr int SPIN_LIMIT = 1 << 24;
constexpr uint32_t PROG_WRAP = NHEADS * (NT - NST) - 1;

__device__ __forceinline__ uint32_t smem_u32(const void* p) { return (uint32_t)__cvta_generic_to_shared(p); }
__device__ __forceinline__ void mbar_init(uint32_t bar, uint32_t cnt) {
    asm volatile("mbarrier.init.shared::cta.b64 [%0], %1;" ::"r"(bar), "r"(cnt) : "memory");
}
__device__ __forceinline__ void mbar_expect_tx(uint32_t bar, uint32_t bytes) {
    asm volatile("mbarrier.arrive.expect_tx.shared::cta.b64 _, [%0], %1;" ::"r"(bar), "r"(bytes) : "memory");
}
__device__ __forceinline__ void mbar_arrive(uint32_t bar) {
    asm volatile("mbarrier.arrive.shared::cta.b64 _, [%0];" ::"r"(bar) : "memory");
}
__device__ __forceinline__ void mbar_arrive_remote(uint32_t bar_cluster_addr) {
    asm volatile("mbarrier.arrive.shared::cluster.b64 _, [%0];" ::"r"(bar_cluster_addr) : "memory");
}
__device__ __forceinline__ void mbar_wait(uint32_t bar, uint32_t parity) {
    uint32_t done = 0;
#pragma unroll 1
    for (int it = 0; it < SPIN_LIMIT; it++) {
        asm volatile("{ .reg .pred p; mbarrier.try_wait.parity.shared::cta.b64 p, [%1], %2; selp.u32 %0, 1, 0, p; }"
                     : "=r"(done) : "r"(bar), "r"(parity) : "memory");
        if (done) return;
    }
    __trap();
}
__device__ __forceinline__ void mbar_wait_cluster(uint32_t bar, uint32_t parity) {
    uint32_t done = 0;
#pragma unroll 1
    for (int it = 0; it < SPIN_LIMIT; it++) {
        asm volatile("{ .reg .pred p; mbarrier.try_wait.parity.acquire.cluster.shared::cta.b64 p, [%1], %2; selp.u32 %0, 1, 0, p; }"
                     : "=r"(done) : "r"(bar), "r"(parity) : "memory");
        if (done) return;
    }
    __trap();
}
__device__ __forceinline__ uint32_t mapa(uint32_t addr, uint32_t rank) {
    uint32_t r;
    asm("mapa.shared::cluster.u32 %0, %1, %2;" : "=r"(r) : "r"(addr), "r"(rank));
    return r;
}
__device__ __forceinline__ void tma2d(uint32_t dst, const CUtensorMap* m, uint32_t bar, int c0, int c1, uint64_t pol) {
    asm volatile("cp.async.bulk.tensor.2d.shared::cluster.global.mbarrier::complete_tx::bytes.L2::cache_hint [%0], [%1, {%3, %4}], [%2], %5;"
                 ::"r"(dst), "l"(m), "r"(bar), "r"(c0), "r"(c1), "l"(pol) : "memory");
}
__device__ __forceinline__ void tma3d(uint32_t dst, const CUtensorMap* m, uint32_t bar, int c0, int c1, int c2) {
    asm volatile("cp.async.bulk.tensor.3d.shared::cluster.global.mbarrier::complete_tx::bytes [%0], [%1, {%3, %4, %5}], [%2];"
                 ::"r"(dst), "l"(m), "r"(bar), "r"(c0), "r"(c1), "r"(c2) : "memory");
}
__device__ __forceinline__ void l2_prefetch(const void* p, uint32_t bytes) {
    asm volatile("cp.async.bulk.prefetch.L2.global [%0], %1;" ::"l"(p), "r"(bytes) : "memory");
}
__device__ __forceinline__ uint64_t make_desc(uint32_t addr) {
    return (uint64_t)((addr & 0x3FFFF) >> 4) | (1ull << 16) | (64ull << 32) | (1ull << 62);
}
__device__ __forceinline__ void wgmma_m64n16k16(float (&d)[8], uint64_t da, uint64_t db, int scale_d) {
    asm volatile("{ .reg .pred p; setp.ne.b32 p, %10, 0;\n"
                 "wgmma.mma_async.sync.aligned.m64n16k16.f32.bf16.bf16 {%0,%1,%2,%3,%4,%5,%6,%7}, %8, %9, p, 1, 1, 1, 0; }"
                 : "+f"(d[0]), "+f"(d[1]), "+f"(d[2]), "+f"(d[3]), "+f"(d[4]), "+f"(d[5]), "+f"(d[6]), "+f"(d[7])
                 : "l"(da), "l"(db), "r"(scale_d));
}
__device__ __forceinline__ void wgmma_fence() { asm volatile("wgmma.fence.sync.aligned;" ::: "memory"); }
__device__ __forceinline__ void wgmma_commit() { asm volatile("wgmma.commit_group.sync.aligned;" ::: "memory"); }
__device__ __forceinline__ void wgmma_wait0() { asm volatile("wgmma.wait_group.sync.aligned 0;" ::: "memory"); }
__device__ __forceinline__ void reg_fence(float (&d)[8]) {
    asm volatile("" : "+f"(d[0]), "+f"(d[1]), "+f"(d[2]), "+f"(d[3]), "+f"(d[4]), "+f"(d[5]), "+f"(d[6]), "+f"(d[7])::"memory");
}
__device__ __forceinline__ float rbf(float x) { return __bfloat162float(__float2bfloat16_rn(x)); }
__device__ __forceinline__ void rbf2(float a, float b, float& ra, float& rb) {
    uint32_t u;
    asm("cvt.rn.bf16x2.f32 %0, %1, %2;" : "=r"(u) : "f"(b), "f"(a));
    ra = __uint_as_float(u << 16);
    rb = __uint_as_float(u & 0xffff0000u);
}

__device__ unsigned int g_prog;
__device__ __forceinline__ void prog_inc() {
    asm volatile("red.relaxed.gpu.global.inc.u32 [%0], %1;" ::"l"(&g_prog), "r"(PROG_WRAP) : "memory");
}

__global__ void __cluster_dims__(2, 1, 1) __launch_bounds__(NTHREADS, 1)
linformer_decode_kernel(const char* __restrict__ kptr, const char* __restrict__ eptr, const char* __restrict__ fptr,
                        const __grid_constant__ CUtensorMap mK, const __grid_constant__ CUtensorMap mV,
                        const __grid_constant__ CUtensorMap mE, const __grid_constant__ CUtensorMap mF,
                        const __nv_bfloat16* __restrict__ q, __nv_bfloat16* __restrict__ out) {
    extern __shared__ unsigned char smem_raw[];
    __shared__ __align__(8) unsigned long long full_bar[NST], empty_bar[NST], score_bar, pace_bar;
    __shared__ __align__(16) float score_part[8][RK];
    __shared__ volatile int s_issued, s_limit;

    const int tid = threadIdx.x;
    const int head = blockIdx.x >> 1, half = blockIdx.x & 1;
    const uint32_t kvbase = (smem_u32(smem_raw) + 1023) & ~1023u;
    const uint32_t ebase = kvbase + NST * KV_BYTES;

    uint64_t pol;
    asm volatile("createpolicy.fractional.L2::evict_first.b64 %0, 1.0;" : "=l"(pol));
    const uint32_t e_off = (blockIdx.x & 15) * (SKV * 2);
    const int e_ph = blockIdx.x >> 4;
    if (tid == 128) {
        asm volatile("cp.async.bulk.prefetch.L2.global.L2::cache_hint [%0], %1, %2;"
                     ::"l"(kptr + (size_t)head * SKV * 256 + half * KV_BYTES), "r"(KV_BYTES), "l"(pol) : "memory");
        l2_prefetch(eptr + e_off + e_ph * (TR * 2), TR * 2);
#pragma unroll 1
        for (int s = 0; s < NST; s++) {
            const uint32_t bar = smem_u32(&full_bar[s]);
            mbar_init(bar, 1);
            mbar_expect_tx(bar, KV_BYTES + E_BYTES);
            tma2d(kvbase + s * KV_BYTES, &mK, bar, half * 64, head * SKV + s * TR, pol);
            tma3d(ebase + s * E_BYTES, &mE, bar, 0, 0, s * (TR / 64));
        }
#pragma unroll 1
        for (int j = e_ph + 8; j < NST + EA; j += 8) l2_prefetch(eptr + e_off + j * (TR * 2), TR * 2);
    }
    if (tid == 0) {
#pragma unroll 1
        for (int s = 0; s < NST; s++) mbar_init(smem_u32(&empty_bar[s]), 4);
        mbar_init(smem_u32(&score_bar), 32);
        mbar_init(smem_u32(&pace_bar), 1);
        s_issued = NST;
        s_limit = NST + LEAD8 / 8;
        asm volatile("fence.mbarrier_init.release.cluster;" ::: "memory");
    }
    __syncthreads();
    asm volatile("barrier.cluster.arrive.relaxed.aligned;" ::: "memory");

    const int warp = __shfl_sync(0xffffffffu, tid >> 5, 0), lane = tid & 31;
    if (warp == 4) {
        if (lane == 0) {
            int s = 0, ph = 0;
#pragma unroll 1
            for (int i = NST; i < NT; i++) {
                const bool isV = i >= TPM;
                const int j = isV ? i - TPM : i;
                const uint32_t bar = smem_u32(&full_bar[s]);
                mbar_wait(smem_u32(&empty_bar[s]), ph);
                if (i > s_limit) {
                    const long long t0 = clock64();
                    while (i > s_limit && clock64() - t0 < MAXW) {}
                }
                mbar_expect_tx(bar, KV_BYTES + E_BYTES);
                tma2d(kvbase + s * KV_BYTES, isV ? &mV : &mK, bar, half * 64, head * SKV + j * TR, pol);
                tma3d(ebase + s * E_BYTES, isV ? &mF : &mE, bar, 0, 0, j * (TR / 64));
                s_issued = i + 1;
                const int jn = i + EA;
                if ((jn & 7) == e_ph && jn < NT) l2_prefetch((jn < TPM ? eptr : fptr) + e_off + (jn & (TPM - 1)) * (TR * 2), TR * 2);
                if (++s == NST) { s = 0; ph ^= 1; }
            }
        }
        __syncwarp();
        asm volatile("barrier.cluster.wait.aligned;" ::: "memory");
    } else if (warp == 5) {
        asm volatile("barrier.cluster.wait.aligned;" ::: "memory");
        if (lane == 0) {
            if (half == 0) {
                const uint32_t lim_peer = mapa(smem_u32((const void*)&s_limit), 1);
                const uint32_t bar_peer = mapa(smem_u32(&pace_bar), 1);
                int reported = NST, last = -1, sent = 0;
#pragma unroll 1
                for (int it = 0; it < SPIN_LIMIT; it++) {
                    const int cur = s_issued;
#pragma unroll 1
                    for (; reported < cur; reported++) prog_inc();
                    int lim = NT;
                    if (cur < NT - 1) {
                        unsigned int gsum;
                        asm volatile("ld.relaxed.gpu.global.u32 %0, [%1];" : "=r"(gsum) : "l"(&g_prog) : "memory");
                        lim = NST + (int)((gsum + LEAD8 * (NHEADS / 8)) / NHEADS);
                    }
                    if (lim != last) {
                        last = lim;
                        s_limit = lim;
                        asm volatile("st.async.shared::cluster.mbarrier::complete_tx::bytes.u32 [%0], %1, [%2];"
                                     ::"r"(lim_peer), "r"(lim), "r"(bar_peer) : "memory");
                        sent += 4;
                    }
                    if (cur == NT) break;
                }
                asm volatile("mbarrier.arrive.expect_tx.shared::cluster.b64 _, [%0], %1;" ::"r"(bar_peer), "r"(sent) : "memory");
            } else {
                mbar_wait(smem_u32(&pace_bar), 0);
            }
        }
    } else {
        const int g = lane >> 2, t = lane & 3;
        const int row0 = warp * 16 + g;
        uint32_t qraw0, qraw1;
        {
            const __nv_bfloat16* qp = q + head * DH + half * 64 + row0;
            asm volatile("ld.global.nc.u16 %0, [%1];" : "=r"(qraw0) : "l"(qp));
            asm volatile("ld.global.nc.u16 %0, [%1+16];" : "=r"(qraw1) : "l"(qp));
        }
        __nv_bfloat16* optr = out + head * DH + half * 64 + row0 + 8 * (t & 1);
        asm volatile("" : "+l"(optr));

        const uint64_t da0 = make_desc(kvbase), db0 = make_desc(ebase);
        float acc[8];
        float p[4];
        int s = 0, ph = 0;
#pragma unroll 1
        for (int i = 0; i < NT; i++) {
            if (i == TPM + TPM / 2) {
                mbar_wait_cluster(smem_u32(&score_bar), 0);
                const int r = lane & 15;
                float sc = 0.f;
#pragma unroll
                for (int w = 0; w < 8; w++) sc += score_part[w][r];
                sc = rbf(rbf(sc) * 0.08838834764831845f);
                float mx = sc;
#pragma unroll
                for (int o = 8; o >= 1; o >>= 1) mx = fmaxf(mx, __shfl_xor_sync(0xffffffffu, mx, o));
                const float ex = expf(sc - mx);
                float sum = ex;
#pragma unroll
                for (int o = 8; o >= 1; o >>= 1) sum += __shfl_xor_sync(0xffffffffu, sum, o);
                const float pr = rbf(ex / sum);
                p[0] = __shfl_sync(0xffffffffu, pr, 2 * t);
                p[1] = __shfl_sync(0xffffffffu, pr, 2 * t + 1);
                p[2] = __shfl_sync(0xffffffffu, pr, 8 + 2 * t);
                p[3] = __shfl_sync(0xffffffffu, pr, 9 + 2 * t);
            }
            mbar_wait(smem_u32(&full_bar[s]), ph);
            const uint64_t da = da0 + s * (KV_BYTES >> 4), db = db0 + s * (E_BYTES >> 4);
            const int first = (i == 0 || i == TPM) ? 0 : 1;
            reg_fence(acc);
            wgmma_fence();
#pragma unroll
            for (int k = 0; k < TR / 16; k++)
                wgmma_m64n16k16(acc, da + k * (2048 >> 4), db + (k >> 2) * (2048 >> 4) + (k & 3) * (32 >> 4), k == 0 ? first : 1);
            wgmma_commit();
            wgmma_wait0();
            reg_fence(acc);
            if (lane == 0) mbar_arrive(smem_u32(&empty_bar[s]));
            if (i == TPM - 1) {
                float sp[4], q0, q1;
                asm volatile("shl.b32 %0, %1, 16;" : "=f"(q0) : "r"(qraw0));
                asm volatile("shl.b32 %0, %1, 16;" : "=f"(q1) : "r"(qraw1));
                sp[0] = q0 * rbf(acc[0]) + q1 * rbf(acc[2]);
                sp[1] = q0 * rbf(acc[1]) + q1 * rbf(acc[3]);
                sp[2] = q0 * rbf(acc[4]) + q1 * rbf(acc[6]);
                sp[3] = q0 * rbf(acc[5]) + q1 * rbf(acc[7]);
#pragma unroll
                for (int o = 4; o <= 16; o <<= 1)
#pragma unroll
                    for (int c = 0; c < 4; c++) sp[c] += __shfl_xor_sync(0xffffffffu, sp[c], o);
                asm volatile("barrier.cluster.wait.aligned;" ::: "memory");
                if (lane < 4) {
                    const uint32_t a = smem_u32(&score_part[half * 4 + warp][2 * t]);
#pragma unroll
                    for (int rk = 0; rk < 2; rk++) {
                        const uint32_t ra = mapa(a, rk);
                        asm volatile("st.shared::cluster.v2.f32 [%0], {%1, %2};" ::"r"(ra), "f"(sp[0]), "f"(sp[1]) : "memory");
                        asm volatile("st.shared::cluster.v2.f32 [%0], {%1, %2};" ::"r"(ra + 32), "f"(sp[2]), "f"(sp[3]) : "memory");
                    }
                    asm volatile("fence.acq_rel.cluster;" ::: "memory");
#pragma unroll
                    for (int rk = 0; rk < 2; rk++) mbar_arrive_remote(mapa(smem_u32(&score_bar), rk));
                }
            }
            if (++s == NST) { s = 0; ph ^= 1; }
        }
        float x[8];
#pragma unroll
        for (int c = 0; c < 8; c += 2) rbf2(acc[c], acc[c + 1], x[c], x[c + 1]);
        const float o0 = (p[0] * x[0] + p[1] * x[1]) + (p[2] * x[4] + p[3] * x[5]);
        const float o1 = (p[0] * x[2] + p[1] * x[3]) + (p[2] * x[6] + p[3] * x[7]);
        float keep = (t & 1) ? o1 : o0;
        keep += __shfl_xor_sync(0xffffffffu, (t & 1) ? o0 : o1, 1);
        keep += __shfl_xor_sync(0xffffffffu, keep, 2);
        if (t < 2) *optr = __float2bfloat16_rn(keep);
    }
}

typedef CUresult (*EncodeTiledFn)(CUtensorMap*, CUtensorMapDataType, cuuint32_t, void*, const cuuint64_t*, const cuuint64_t*,
                                  const cuuint32_t*, const cuuint32_t*, CUtensorMapInterleave, CUtensorMapSwizzle,
                                  CUtensorMapL2promotion, CUtensorMapFloatOOBfill);

void encode_kv(EncodeTiledFn enc, CUtensorMap* m, void* p) {
    cuuint64_t dims[2] = {(cuuint64_t)DH, (cuuint64_t)NHEADS * SKV};
    cuuint64_t str[1] = {DH * 2};
    cuuint32_t box[2] = {64, TR};
    cuuint32_t es[2] = {1, 1};
    enc(m, CU_TENSOR_MAP_DATA_TYPE_BFLOAT16, 2, p, dims, str, box, es, CU_TENSOR_MAP_INTERLEAVE_NONE,
        CU_TENSOR_MAP_SWIZZLE_128B, CU_TENSOR_MAP_L2_PROMOTION_L2_256B, CU_TENSOR_MAP_FLOAT_OOB_FILL_NONE);
}
void encode_ef(EncodeTiledFn enc, CUtensorMap* m, void* p) {
    cuuint64_t dims[3] = {64, (cuuint64_t)RK, (cuuint64_t)SKV / 64};
    cuuint64_t str[2] = {SKV * 2, 128};
    cuuint32_t box[3] = {64, RK, TR / 64};
    cuuint32_t es[3] = {1, 1, 1};
    enc(m, CU_TENSOR_MAP_DATA_TYPE_BFLOAT16, 3, p, dims, str, box, es, CU_TENSOR_MAP_INTERLEAVE_NONE,
        CU_TENSOR_MAP_SWIZZLE_128B, CU_TENSOR_MAP_L2_PROMOTION_NONE, CU_TENSOR_MAP_FLOAT_OOB_FILL_NONE);
}

}

extern "C" void kernel_launch(void* const* d_in, const int* in_sizes, int n_in, void* d_out, int out_size) {
    (void)in_sizes; (void)n_in; (void)out_size;
    static EncodeTiledFn enc = nullptr;
    if (!enc) {
        cudaDriverEntryPointQueryResult qr;
        cudaGetDriverEntryPoint("cuTensorMapEncodeTiled", (void**)&enc, cudaEnableDefault, &qr);
        cudaFuncSetAttribute(linformer_decode_kernel, cudaFuncAttributeMaxDynamicSharedMemorySize, SMEM_BYTES);
    }
    CUtensorMap mK, mV, mE, mF;
    encode_kv(enc, &mK, d_in[1]);
    encode_kv(enc, &mV, d_in[2]);
    encode_ef(enc, &mE, d_in[3]);
    encode_ef(enc, &mF, d_in[4]);
    linformer_decode_kernel<<<2 * NHEADS, NTHREADS, SMEM_BYTES, cudaStreamPerThread>>>(
        (const char*)d_in[1], (const char*)d_in[3], (const char*)d_in[4], mK, mV, mE, mF, (const __nv_bfloat16*)d_in[0], (__nv_bfloat16*)d_out);
}
```

```cpp
#include <cuda_runtime.h>
#include <cuda_bf16.h>
#include <cuda.h>
#include <stdint.h>

namespace {

constexpr int SKV = 16384, DH = 128, RK = 16, NHEADS = 64;
constexpr int TR = 128;
constexpr int NST = 8;
constexpr int LEAD8 = 10;
constexpr int MAXW = 900;
constexpr int EA = 16;
constexpr int TPM = SKV / TR;
constexpr int NT = 2 * TPM;
constexpr int KV_BYTES = TR * 128;
constexpr int E_BYTES = TR * RK * 2;
constexpr int SMEM_BYTES = NST * (KV_BYTES + E_BYTES) + 1024;
constexpr int NTHREADS = 192;
constexpr int SPIN_LIMIT = 1 << 24;
constexpr uint32_t PROG_WRAP = NHEADS * (NT - NST) - 1;

__device__ __forceinline__ uint32_t smem_u32(const void* p) { return (uint32_t)__cvta_generic_to_shared(p); }
__device__ __forceinline__ void mbar_init(uint32_t bar, uint32_t cnt) {
    asm volatile("mbarrier.init.shared::cta.b64 [%0], %1;" ::"r"(bar), "r"(cnt) : "memory");
}
__device__ __forceinline__ void mbar_expect_tx(uint32_t bar, uint32_t bytes) {
    asm volatile("mbarrier.arrive.expect_tx.shared::cta.b64 _, [%0], %1;" ::"r"(bar), "r"(bytes) : "memory");
}
__device__ __forceinline__ void mbar_arrive(uint32_t bar) {
    asm volatile("mbarrier.arrive.shared::cta.b64 _, [%0];" ::"r"(bar) : "memory");
}
__device__ __forceinline__ void mbar_arrive_remote(uint32_t bar_cluster_addr) {
    asm volatile("mbarrier.arrive.shared::cluster.b64 _, [%0];" ::"r"(bar_cluster_addr) : "memory");
}
__device__ __forceinline__ void mbar_wait(uint32_t bar, uint32_t parity) {
    uint32_t done = 0;
#pragma unroll 1
    for (int it = 0; it < SPIN_LIMIT; it++) {
        asm volatile("{ .reg .pred p; mbarrier.try_wait.parity.shared::cta.b64 p, [%1], %2; selp.u32 %0, 1, 0, p; }"
                     : "=r"(done) : "r"(bar), "r"(parity) : "memory");
        if (done) return;
    }
    __trap();
}
__device__ __forceinline__ void mbar_wait_cluster(uint32_t bar, uint32_t parity) {
    uint32_t done = 0;
#pragma unroll 1
    for (int it = 0; it < SPIN_LIMIT; it++) {
        asm volatile("{ .reg .pred p; mbarrier.try_wait.parity.acquire.cluster.shared::cta.b64 p, [%1], %2; selp.u32 %0, 1, 0, p; }"
                     : "=r"(done) : "r"(bar), "r"(parity) : "memory");
        if (done) return;
    }
    __trap();
}
__device__ __forceinline__ uint32_t mapa(uint32_t addr, uint32_t rank) {
    uint32_t r;
    asm("mapa.shared::cluster.u32 %0, %1, %2;" : "=r"(r) : "r"(addr), "r"(rank));
    return r;
}
__device__ __forceinline__ void tma2d(uint32_t dst, const CUtensorMap* m, uint32_t bar, int c0, int c1, uint64_t pol) {
    asm volatile("cp.async.bulk.tensor.2d.shared::cluster.global.mbarrier::complete_tx::bytes.L2::cache_hint [%0], [%1, {%3, %4}], [%2], %5;"
                 ::"r"(dst), "l"(m), "r"(bar), "r"(c0), "r"(c1), "l"(pol) : "memory");
}
__device__ __forceinline__ void tma3d(uint32_t dst, const CUtensorMap* m, uint32_t bar, int c0, int c1, int c2) {
    asm volatile("cp.async.bulk.tensor.3d.shared::cluster.global.mbarrier::complete_tx::bytes [%0], [%1, {%3, %4, %5}], [%2];"
                 ::"r"(dst), "l"(m), "r"(bar), "r"(c0), "r"(c1), "r"(c2) : "memory");
}
__device__ __forceinline__ void l2_prefetch(const void* p, uint32_t bytes) {
    asm volatile("cp.async.bulk.prefetch.L2.global [%0], %1;" ::"l"(p), "r"(bytes) : "memory");
}
__device__ __forceinline__ uint64_t make_desc(uint32_t addr) {
    return (uint64_t)((addr & 0x3FFFF) >> 4) | (1ull << 16) | (64ull << 32) | (1ull << 62);
}
__device__ __forceinline__ void wgmma_m64n16k16(float (&d)[8], uint64_t da, uint64_t db, int scale_d) {
    asm volatile("{ .reg .pred p; setp.ne.b32 p, %10, 0;\n"
                 "wgmma.mma_async.sync.aligned.m64n16k16.f32.bf16.bf16 {%0,%1,%2,%3,%4,%5,%6,%7}, %8, %9, p, 1, 1, 1, 0; }"
                 : "+f"(d[0]), "+f"(d[1]), "+f"(d[2]), "+f"(d[3]), "+f"(d[4]), "+f"(d[5]), "+f"(d[6]), "+f"(d[7])
                 : "l"(da), "l"(db), "r"(scale_d));
}
__device__ __forceinline__ void wgmma_fence() { asm volatile("wgmma.fence.sync.aligned;" ::: "memory"); }
__device__ __forceinline__ void wgmma_commit() { asm volatile("wgmma.commit_group.sync.aligned;" ::: "memory"); }
__device__ __forceinline__ void wgmma_wait0() { asm volatile("wgmma.wait_group.sync.aligned 0;" ::: "memory"); }
__device__ __forceinline__ void reg_fence(float (&d)[8]) {
    asm volatile("" : "+f"(d[0]), "+f"(d[1]), "+f"(d[2]), "+f"(d[3]), "+f"(d[4]), "+f"(d[5]), "+f"(d[6]), "+f"(d[7])::"memory");
}
__device__ __forceinline__ float rbf(float x) { return __bfloat162float(__float2bfloat16_rn(x)); }
__device__ __forceinline__ void rbf2(float a, float b, float& ra, float& rb) {
    uint32_t u;
    asm("cvt.rn.bf16x2.f32 %0, %1, %2;" : "=r"(u) : "f"(b), "f"(a));
    ra = __uint_as_float(u << 16);
    rb = __uint_as_float(u & 0xffff0000u);
}

__device__ unsigned int g_prog;
__device__ __forceinline__ void prog_inc() {
    asm volatile("red.relaxed.gpu.global.inc.u32 [%0], %1;" ::"l"(&g_prog), "r"(PROG_WRAP) : "memory");
}

__global__ void __cluster_dims__(2, 1, 1) __launch_bounds__(NTHREADS, 1)
linformer_decode_kernel(const char* __restrict__ kptr, const char* __restrict__ eptr, const char* __restrict__ fptr,
                        const __grid_constant__ CUtensorMap mK, const __grid_constant__ CUtensorMap mV,
                        const __grid_constant__ CUtensorMap mE, const __grid_constant__ CUtensorMap mF,
                        const __nv_bfloat16* __restrict__ q, __nv_bfloat16* __restrict__ out) {
    extern __shared__ unsigned char smem_raw[];
    __shared__ __align__(8) unsigned long long full_bar[NST], empty_bar[NST], score_bar, pace_bar;
    __shared__ __align__(16) float score_part[8][RK];
    __shared__ volatile int s_issued, s_limit;

    const int tid = threadIdx.x;
    const int head = blockIdx.x >> 1, half = blockIdx.x & 1;
    const uint32_t kvbase = (smem_u32(smem_raw) + 1023) & ~1023u;
    const uint32_t ebase = kvbase + NST * KV_BYTES;

    uint64_t pol;
    asm volatile("createpolicy.fractional.L2::evict_first.b64 %0, 1.0;" : "=l"(pol));
    const uint32_t e_off = (blockIdx.x & 15) * (SKV * 2);
    const int e_ph = blockIdx.x >> 4;
    if (tid == 128) {
        asm volatile("cp.async.bulk.prefetch.L2.global.L2::cache_hint [%0], %1, %2;"
                     ::"l"(kptr + (size_t)head * SKV * 256 + half * KV_BYTES), "r"(KV_BYTES), "l"(pol) : "memory");
        l2_prefetch(eptr + e_off + e_ph * (TR * 2), TR * 2);
#pragma unroll 1
        for (int s = 0; s < NST; s++) {
            const uint32_t bar = smem_u32(&full_bar[s]);
            mbar_init(bar, 1);
            mbar_expect_tx(bar, KV_BYTES + E_BYTES);
            tma2d(kvbase + s * KV_BYTES, &mK, bar, half * 64, head * SKV + s * TR, pol);
            tma3d(ebase + s * E_BYTES, &mE, bar, 0, 0, s * (TR / 64));
        }
#pragma unroll 1
        for (int j = e_ph + 8; j < NST + EA; j += 8) l2_prefetch(eptr + e_off + j * (TR * 2), TR * 2);
    }
    if (tid == 0) {
#pragma unroll 1
        for (int s = 0; s < NST; s++) mbar_init(smem_u32(&empty_bar[s]), 4);
        mbar_init(smem_u32(&score_bar), 32);
        mbar_init(smem_u32(&pace_bar), 1);
        s_issued = NST;
        s_limit = NST + LEAD8 / 8;
        asm volatile("fence.mbarrier_init.release.cluster;" ::: "memory");
    }
    __syncthreads();
    asm volatile("barrier.cluster.arrive.relaxed.aligned;" ::: "memory");

    const int warp = __shfl_sync(0xffffffffu, tid >> 5, 0), lane = tid & 31;
    if (warp == 4) {
        if (lane == 0) {
            int s = 0, ph = 0;
#pragma unroll 1
            for (int i = NST; i < NT; i++) {
                const bool isV = i >= TPM;
                const int j = isV ? i - TPM : i;
                const uint32_t bar = smem_u32(&full_bar[s]);
                mbar_wait(smem_u32(&empty_bar[s]), ph);
                if (i > s_limit) {
                    const long long t0 = clock64();
                    while (i > s_limit && clock64() - t0 < MAXW) {}
                }
                mbar_expect_tx(bar, KV_BYTES + E_BYTES);
                tma2d(kvbase + s * KV_BYTES, isV ? &mV : &mK, bar, half * 64, head * SKV + j * TR, pol);
                tma3d(ebase + s * E_BYTES, isV ? &mF : &mE, bar, 0, 0, j * (TR / 64));
                s_issued = i + 1;
                const int jn = i + EA;
                if ((jn & 7) == e_ph && jn < NT) l2_prefetch((jn < TPM ? eptr : fptr) + e_off + (jn & (TPM - 1)) * (TR * 2), TR * 2);
                if (++s == NST) { s = 0; ph ^= 1; }
            }
        }
        __syncwarp();
        asm volatile("barrier.cluster.wait.aligned;" ::: "memory");
    } else if (warp == 5) {
        asm volatile("barrier.cluster.wait.aligned;" ::: "memory");
        if (lane == 0) {
            if (half == 0) {
                const uint32_t lim_peer = mapa(smem_u32((const void*)&s_limit), 1);
                const uint32_t bar_peer = mapa(smem_u32(&pace_bar), 1);
                int reported = NST, last = -1, sent = 0;
#pragma unroll 1
                for (int it = 0; it < SPIN_LIMIT; it++) {
                    const int cur = s_issued;
#pragma unroll 1
                    for (; reported < cur; reported++) prog_inc();
                    int lim = NT;
                    if (cur < NT - 1) {
                        unsigned int gsum;
                        asm volatile("ld.relaxed.gpu.global.u32 %0, [%1];" : "=r"(gsum) : "l"(&g_prog) : "memory");
                        lim = NST + (int)((gsum + LEAD8 * (NHEADS / 8)) / NHEADS);
                    }
                    if (lim > last) {
                        last = lim;
                        s_limit = lim;
                        asm volatile("st.async.shared::cluster.mbarrier::complete_tx::bytes.u32 [%0], %1, [%2];"
                                     ::"r"(lim_peer), "r"(lim), "r"(bar_peer) : "memory");
                        sent += 4;
                    }
                    if (cur == NT) break;
                }
                asm volatile("mbarrier.arrive.expect_tx.shared::cluster.b64 _, [%0], %1;" ::"r"(bar_peer), "r"(sent) : "memory");
            } else {
                mbar_wait(smem_u32(&pace_bar), 0);
            }
        }
    } else {
        const int g = lane >> 2, t = lane & 3;
        const int row0 = warp * 16 + g;
        uint32_t qraw0, qraw1;
        {
            const __nv_bfloat16* qp = q + head * DH + half * 64 + row0;
            asm volatile("ld.global.nc.u16 %0, [%1];" : "=r"(qraw0) : "l"(qp));
            asm volatile("ld.global.nc.u16 %0, [%1+16];" : "=r"(qraw1) : "l"(qp));
        }
        __nv_bfloat16* optr = out + head * DH + half * 64 + row0 + 8 * (t & 1);
        asm volatile("" : "+l"(optr));

        const uint64_t da0 = make_desc(kvbase), db0 = make_desc(ebase);
        float acc[8];
        float p[4];
        int s = 0, ph = 0;
#pragma unroll 1
        for (int i = 0; i < NT; i++) {
            if (i == TPM + TPM / 2) {
                mbar_wait_cluster(smem_u32(&score_bar), 0);
                const int r = lane & 15;
                float sc = 0.f;
#pragma unroll
                for (int w = 0; w < 8; w++) sc += score_part[w][r];
                sc = rbf(rbf(sc) * 0.08838834764831845f);
                float mx = sc;
#pragma unroll
                for (int o = 8; o >= 1; o >>= 1) mx = fmaxf(mx, __shfl_xor_sync(0xffffffffu, mx, o));
                const float ex = expf(sc - mx);
                float sum = ex;
#pragma unroll
                for (int o = 8; o >= 1; o >>= 1) sum += __shfl_xor_sync(0xffffffffu, sum, o);
                const float pr = rbf(ex / sum);
                p[0] = __shfl_sync(0xffffffffu, pr, 2 * t);
                p[1] = __shfl_sync(0xffffffffu, pr, 2 * t + 1);
                p[2] = __shfl_sync(0xffffffffu, pr, 8 + 2 * t);
                p[3] = __shfl_sync(0xffffffffu, pr, 9 + 2 * t);
            }
            mbar_wait(smem_u32(&full_bar[s]), ph);
            const uint64_t da = da0 + s * (KV_BYTES >> 4), db = db0 + s * (E_BYTES >> 4);
            const int first = (i == 0 || i == TPM) ? 0 : 1;
            reg_fence(acc);
            wgmma_fence();
#pragma unroll
            for (int k = 0; k < TR / 16; k++)
                wgmma_m64n16k16(acc, da + k * (2048 >> 4), db + (k >> 2) * (2048 >> 4) + (k & 3) * (32 >> 4), k == 0 ? first : 1);
            wgmma_commit();
            wgmma_wait0();
            reg_fence(acc);
            if (lane == 0) mbar_arrive(smem_u32(&empty_bar[s]));
            if (i == TPM - 1) {
                float sp[4], q0, q1;
                asm volatile("shl.b32 %0, %1, 16;" : "=f"(q0) : "r"(qraw0));
                asm volatile("shl.b32 %0, %1, 16;" : "=f"(q1) : "r"(qraw1));
                sp[0] = q0 * rbf(acc[0]) + q1 * rbf(acc[2]);
                sp[1] = q0 * rbf(acc[1]) + q1 * rbf(acc[3]);
                sp[2] = q0 * rbf(acc[4]) + q1 * rbf(acc[6]);
                sp[3] = q0 * rbf(acc[5]) + q1 * rbf(acc[7]);
#pragma unroll
                for (int o = 4; o <= 16; o <<= 1)
#pragma unroll
                    for (int c = 0; c < 4; c++) sp[c] += __shfl_xor_sync(0xffffffffu, sp[c], o);
                asm volatile("barrier.cluster.wait.aligned;" ::: "memory");
                if (lane < 4) {
                    const uint32_t a = smem_u32(&score_part[half * 4 + warp][2 * t]);
#pragma unroll
                    for (int rk = 0; rk < 2; rk++) {
                        const uint32_t ra = mapa(a, rk);
                        asm volatile("st.shared::cluster.v2.f32 [%0], {%1, %2};" ::"r"(ra), "f"(sp[0]), "f"(sp[1]) : "memory");
                        asm volatile("st.shared::cluster.v2.f32 [%0], {%1, %2};" ::"r"(ra + 32), "f"(sp[2]), "f"(sp[3]) : "memory");
                    }
                    asm volatile("fence.acq_rel.cluster;" ::: "memory");
#pragma unroll
                    for (int rk = 0; rk < 2; rk++) mbar_arrive_remote(mapa(smem_u32(&score_bar), rk));
                }
            }
            if (++s == NST) { s = 0; ph ^= 1; }
        }
        float x[8];
#pragma unroll
        for (int c = 0; c < 8; c += 2) rbf2(acc[c], acc[c + 1], x[c], x[c + 1]);
        const float o0 = (p[0] * x[0] + p[1] * x[1]) + (p[2] * x[4] + p[3] * x[5]);
        const float o1 = (p[0] * x[2] + p[1] * x[3]) + (p[2] * x[6] + p[3] * x[7]);
        float keep = (t & 1) ? o1 : o0;
        keep += __shfl_xor_sync(0xffffffffu, (t & 1) ? o0 : o1, 1);
        keep += __shfl_xor_sync(0xffffffffu, keep, 2);
        if (t < 2) asm volatile("st.global.b16 [%0], %1;" ::"l"(optr), "h"(__bfloat16_as_ushort(__float2bfloat16_rn(keep))) : "memory");
    }
}

typedef CUresult (*EncodeTiledFn)(CUtensorMap*, CUtensorMapDataType, cuuint32_t, void*, const cuuint64_t*, const cuuint64_t*,
                                  const cuuint32_t*, const cuuint32_t*, CUtensorMapInterleave, CUtensorMapSwizzle,
                                  CUtensorMapL2promotion, CUtensorMapFloatOOBfill);

void encode_kv(EncodeTiledFn enc, CUtensorMap* m, void* p) {
    cuuint64_t dims[2] = {(cuuint64_t)DH, (cuuint64_t)NHEADS * SKV};
    cuuint64_t str[1] = {DH * 2};
    cuuint32_t box[2] = {64, TR};
    cuuint32_t es[2] = {1, 1};
    enc(m, CU_TENSOR_MAP_DATA_TYPE_BFLOAT16, 2, p, dims, str, box, es, CU_TENSOR_MAP_INTERLEAVE_NONE,
        CU_TENSOR_MAP_SWIZZLE_128B, CU_TENSOR_MAP_L2_PROMOTION_L2_256B, CU_TENSOR_MAP_FLOAT_OOB_FILL_NONE);
}
void encode_ef(EncodeTiledFn enc, CUtensorMap* m, void* p) {
    cuuint64_t dims[3] = {64, (cuuint64_t)RK, (cuuint64_t)SKV / 64};
    cuuint64_t str[2] = {SKV * 2, 128};
    cuuint32_t box[3] = {64, RK, TR / 64};
    cuuint32_t es[3] = {1, 1, 1};
    enc(m, CU_TENSOR_MAP_DATA_TYPE_BFLOAT16, 3, p, dims, str, box, es, CU_TENSOR_MAP_INTERLEAVE_NONE,
        CU_TENSOR_MAP_SWIZZLE_128B, CU_TENSOR_MAP_L2_PROMOTION_NONE, CU_TENSOR_MAP_FLOAT_OOB_FILL_NONE);
}

}

extern "C" void kernel_launch(void* const* d_in, const int* in_sizes, int n_in, void* d_out, int out_size) {
    (void)in_sizes; (void)n_in; (void)out_size;
    static EncodeTiledFn enc = nullptr;
    if (!enc) {
        cudaDriverEntryPointQueryResult qr;
        cudaGetDriverEntryPoint("cuTensorMapEncodeTiled", (void**)&enc, cudaEnableDefault, &qr);
        if (!enc) return;
        cudaFuncSetAttribute(linformer_decode_kernel, cudaFuncAttributeMaxDynamicSharedMemorySize, SMEM_BYTES);
    }
    CUtensorMap mK, mV, mE, mF;
    encode_kv(enc, &mK, d_in[1]);
    encode_kv(enc, &mV, d_in[2]);
    encode_ef(enc, &mE, d_in[3]);
    encode_ef(enc, &mF, d_in[4]);
    linformer_decode_kernel<<<2 * NHEADS, NTHREADS, SMEM_BYTES, cudaStreamPerThread>>>(
        (const char*)d_in[1], (const char*)d_in[3], (const char*)d_in[4], mK, mV, mE, mF, (const __nv_bfloat16*)d_in[0], (__nv_bfloat16*)d_out);
}
```

```cpp
#include <cuda_runtime.h>
#include <cuda_bf16.h>
#include <cuda.h>
#include <stdint.h>

namespace {

constexpr int SKV = 16384, DH = 128, RK = 16, NHEADS = 64;
constexpr int TR = 128;
constexpr int NST = 8;
constexpr int LEAD8 = 10;
constexpr int MAXW = 900;
constexpr int EA = 16;
constexpr int TPM = SKV / TR;
constexpr int NT = 2 * TPM;
constexpr int KV_BYTES = TR * 128;
constexpr int E_BYTES = TR * RK * 2;
constexpr int SMEM_BYTES = NST * (KV_BYTES + E_BYTES) + 1024;
constexpr int NTHREADS = 192;
constexpr int SPIN_LIMIT = 1 << 24;
constexpr uint32_t PROG_WRAP = NHEADS * (NT - NST) - 1;

__device__ __forceinline__ uint32_t smem_u32(const void* p) { return (uint32_t)__cvta_generic_to_shared(p); }
__device__ __forceinline__ void mbar_init(uint32_t bar, uint32_t cnt) {
    asm volatile("mbarrier.init.shared::cta.b64 [%0], %1;" ::"r"(bar), "r"(cnt) : "memory");
}
__device__ __forceinline__ void mbar_expect_tx(uint32_t bar, uint32_t bytes) {
    asm volatile("mbarrier.arrive.expect_tx.shared::cta.b64 _, [%0], %1;" ::"r"(bar), "r"(bytes) : "memory");
}
__device__ __forceinline__ void mbar_arrive(uint32_t bar) {
    asm volatile("mbarrier.arrive.shared::cta.b64 _, [%0];" ::"r"(bar) : "memory");
}
__device__ __forceinline__ void mbar_wait(uint32_t bar, uint32_t parity) {
    uint32_t done = 0;
#pragma unroll 1
    for (int it = 0; it < SPIN_LIMIT; it++) {
        asm volatile("{ .reg .pred p; mbarrier.try_wait.parity.shared::cta.b64 p, [%1], %2; selp.u32 %0, 1, 0, p; }"
                     : "=r"(done) : "r"(bar), "r"(parity) : "memory");
        if (done) return;
    }
    __trap();
}
__device__ __forceinline__ void mbar_wait_long(uint32_t bar, uint32_t parity) {
    uint32_t done = 0;
#pragma unroll 1
    for (int it = 0; it < SPIN_LIMIT; it++) {
        asm volatile("{ .reg .pred p; mbarrier.try_wait.parity.shared::cta.b64 p, [%1], %2; selp.u32 %0, 1, 0, p; }"
                     : "=r"(done) : "r"(bar), "r"(parity) : "memory");
        if (done) return;
        __nanosleep(128);
    }
    __trap();
}
__device__ __forceinline__ void mbar_wait_cluster(uint32_t bar, uint32_t parity) {
    uint32_t done = 0;
#pragma unroll 1
    for (int it = 0; it < SPIN_LIMIT; it++) {
        asm volatile("{ .reg .pred p; mbarrier.try_wait.parity.acquire.cluster.shared::cta.b64 p, [%1], %2; selp.u32 %0, 1, 0, p; }"
                     : "=r"(done) : "r"(bar), "r"(parity) : "memory");
        if (done) return;
    }
    __trap();
}
__device__ __forceinline__ uint32_t mapa(uint32_t addr, uint32_t rank) {
    uint32_t r;
    asm("mapa.shared::cluster.u32 %0, %1, %2;" : "=r"(r) : "r"(addr), "r"(rank));
    return r;
}
__device__ __forceinline__ void tma2d(uint32_t dst, const CUtensorMap* m, uint32_t bar, int c0, int c1, uint64_t pol) {
    asm volatile("cp.async.bulk.tensor.2d.shared::cluster.global.mbarrier::complete_tx::bytes.L2::cache_hint [%0], [%1, {%3, %4}], [%2], %5;"
                 ::"r"(dst), "l"(m), "r"(bar), "r"(c0), "r"(c1), "l"(pol) : "memory");
}
__device__ __forceinline__ void tma3d(uint32_t dst, const CUtensorMap* m, uint32_t bar, int c0, int c1, int c2) {
    asm volatile("cp.async.bulk.tensor.3d.shared::cluster.global.mbarrier::complete_tx::bytes [%0], [%1, {%3, %4, %5}], [%2];"
                 ::"r"(dst), "l"(m), "r"(bar), "r"(c0), "r"(c1), "r"(c2) : "memory");
}
__device__ __forceinline__ void l2_prefetch(const void* p, uint32_t bytes) {
    asm volatile("cp.async.bulk.prefetch.L2.global [%0], %1;" ::"l"(p), "r"(bytes) : "memory");
}
__device__ __forceinline__ uint64_t make_desc(uint32_t addr) {
    return (uint64_t)((addr & 0x3FFFF) >> 4) | (1ull << 16) | (64ull << 32) | (1ull << 62);
}
__device__ __forceinline__ void wgmma_m64n16k16(float (&d)[8], uint64_t da, uint64_t db, int scale_d) {
    asm volatile("{ .reg .pred p; setp.ne.b32 p, %10, 0;\n"
                 "wgmma.mma_async.sync.aligned.m64n16k16.f32.bf16.bf16 {%0,%1,%2,%3,%4,%5,%6,%7}, %8, %9, p, 1, 1, 1, 0; }"
                 : "+f"(d[0]), "+f"(d[1]), "+f"(d[2]), "+f"(d[3]), "+f"(d[4]), "+f"(d[5]), "+f"(d[6]), "+f"(d[7])
                 : "l"(da), "l"(db), "r"(scale_d));
}
__device__ __forceinline__ void wgmma_fence() { asm volatile("wgmma.fence.sync.aligned;" ::: "memory"); }
__device__ __forceinline__ void wgmma_commit() { asm volatile("wgmma.commit_group.sync.aligned;" ::: "memory"); }
__device__ __forceinline__ void wgmma_wait0() { asm volatile("wgmma.wait_group.sync.aligned 0;" ::: "memory"); }
__device__ __forceinline__ void reg_fence(float (&d)[8]) {
    asm volatile("" : "+f"(d[0]), "+f"(d[1]), "+f"(d[2]), "+f"(d[3]), "+f"(d[4]), "+f"(d[5]), "+f"(d[6]), "+f"(d[7])::"memory");
}
__device__ __forceinline__ float rbf(float x) { return __bfloat162float(__float2bfloat16_rn(x)); }
__device__ __forceinline__ void rbf2(float a, float b, float& ra, float& rb) {
    uint32_t u;
    asm("cvt.rn.bf16x2.f32 %0, %1, %2;" : "=r"(u) : "f"(b), "f"(a));
    ra = __uint_as_float(u << 16);
    rb = __uint_as_float(u & 0xffff0000u);
}

__device__ unsigned int g_prog;
__device__ __forceinline__ void prog_inc() {
    asm volatile("red.relaxed.gpu.global.inc.u32 [%0], %1;" ::"l"(&g_prog), "r"(PROG_WRAP) : "memory");
}

__global__ void __cluster_dims__(2, 1, 1) __launch_bounds__(NTHREADS, 1)
linformer_decode_kernel(const char* __restrict__ kptr, const char* __restrict__ eptr, const char* __restrict__ fptr,
                        const __grid_constant__ CUtensorMap mK, const __grid_constant__ CUtensorMap mV,
                        const __grid_constant__ CUtensorMap mE, const __grid_constant__ CUtensorMap mF,
                        const __nv_bfloat16* __restrict__ q, __nv_bfloat16* __restrict__ out) {
    extern __shared__ unsigned char smem_raw[];
    __shared__ __align__(8) unsigned long long full_bar[NST], empty_bar[NST], score_bar, pace_bar;
    __shared__ __align__(16) float score_part[8][RK];
    __shared__ volatile int s_issued, s_limit;

    const int tid = threadIdx.x;
    const int head = blockIdx.x >> 1, half = blockIdx.x & 1;
    const uint32_t kvbase = (smem_u32(smem_raw) + 1023) & ~1023u;
    const uint32_t ebase = kvbase + NST * KV_BYTES;

    uint64_t pol;
    asm volatile("createpolicy.fractional.L2::evict_first.b64 %0, 1.0;" : "=l"(pol));
    const uint32_t e_off = (blockIdx.x & 15) * (SKV * 2);
    const int e_ph = blockIdx.x >> 4;
    if (tid == 128) {
        asm volatile("cp.async.bulk.prefetch.L2.global.L2::cache_hint [%0], %1, %2;"
                     ::"l"(kptr + (size_t)head * SKV * 256 + half * KV_BYTES), "r"(KV_BYTES), "l"(pol) : "memory");
        l2_prefetch(eptr + e_off + e_ph * (TR * 2), TR * 2);
#pragma unroll 1
        for (int s = 0; s < NST; s++) {
            const uint32_t bar = smem_u32(&full_bar[s]);
            mbar_init(bar, 1);
            mbar_expect_tx(bar, KV_BYTES + E_BYTES);
            tma2d(kvbase + s * KV_BYTES, &mK, bar, half * 64, head * SKV + s * TR, pol);
            tma3d(ebase + s * E_BYTES, &mE, bar, 0, 0, s * (TR / 64));
        }
#pragma unroll 1
        for (int j = e_ph + 8; j < NST + EA; j += 8) l2_prefetch(eptr + e_off + j * (TR * 2), TR * 2);
    }
    if (tid == 0) {
#pragma unroll 1
        for (int s = 0; s < NST; s++) mbar_init(smem_u32(&empty_bar[s]), 4);
        mbar_init(smem_u32(&score_bar), 1);
        mbar_expect_tx(smem_u32(&score_bar), sizeof(score_part));
        mbar_init(smem_u32(&pace_bar), 1);
        s_issued = NST;
        s_limit = NST + LEAD8 / 8;
        asm volatile("fence.mbarrier_init.release.cluster;" ::: "memory");
    }
    __syncthreads();
    asm volatile("barrier.cluster.arrive.relaxed.aligned;" ::: "memory");

    const int warp = __shfl_sync(0xffffffffu, tid >> 5, 0), lane = tid & 31;
    if (warp == 4) {
        if (lane == 0) {
            int s = 0, ph = 0;
#pragma unroll 1
            for (int i = NST; i < NT; i++) {
                const bool isV = i >= TPM;
                const int j = isV ? i - TPM : i;
                const uint32_t bar = smem_u32(&full_bar[s]);
                mbar_wait(smem_u32(&empty_bar[s]), ph);
                if (i > s_limit) {
                    const long long t0 = clock64();
                    while (i > s_limit && clock64() - t0 < MAXW) {}
                }
                mbar_expect_tx(bar, KV_BYTES + E_BYTES);
                tma2d(kvbase + s * KV_BYTES, isV ? &mV : &mK, bar, half * 64, head * SKV + j * TR, pol);
                tma3d(ebase + s * E_BYTES, isV ? &mF : &mE, bar, 0, 0, j * (TR / 64));
                s_issued = i + 1;
                const int jn = i + EA;
                if ((jn & 7) == e_ph && jn < NT) l2_prefetch((jn < TPM ? eptr : fptr) + e_off + (jn & (TPM - 1)) * (TR * 2), TR * 2);
                if (++s == NST) { s = 0; ph ^= 1; }
            }
        }
        __syncwarp();
        asm volatile("barrier.cluster.wait.aligned;" ::: "memory");
    } else if (warp == 5) {
        asm volatile("barrier.cluster.wait.aligned;" ::: "memory");
        if (lane == 0) {
            if (half == 0) {
                const uint32_t lim_peer = mapa(smem_u32((const void*)&s_limit), 1);
                const uint32_t bar_peer = mapa(smem_u32(&pace_bar), 1);
                int reported = NST, last = -1, sent = 0;
#pragma unroll 1
                for (int it = 0; it < SPIN_LIMIT; it++) {
                    const int cur = s_issued;
#pragma unroll 1
                    for (; reported < cur; reported++) prog_inc();
                    int lim = NT;
                    if (cur < NT - 1) {
                        unsigned int gsum;
                        asm volatile("ld.relaxed.gpu.global.u32 %0, [%1];" : "=r"(gsum) : "l"(&g_prog) : "memory");
                        lim = NST + (int)((gsum + LEAD8 * (NHEADS / 8)) / NHEADS);
                    }
                    if (lim > last) {
                        last = lim;
                        s_limit = lim;
                        asm volatile("st.async.shared::cluster.mbarrier::complete_tx::bytes.u32 [%0], %1, [%2];"
                                     ::"r"(lim_peer), "r"(lim), "r"(bar_peer) : "memory");
                        sent += 4;
                    }
                    if (cur == NT) break;
                }
                asm volatile("mbarrier.arrive.expect_tx.shared::cluster.b64 _, [%0], %1;" ::"r"(bar_peer), "r"(sent) : "memory");
            } else {
                mbar_wait_long(smem_u32(&pace_bar), 0);
            }
        }
    } else {
        const int g = lane >> 2, t = lane & 3;
        const int row0 = warp * 16 + g;
        uint32_t qraw0, qraw1;
        {
            const __nv_bfloat16* qp = q + head * DH + half * 64 + row0;
            asm volatile("ld.global.nc.u16 %0, [%1];" : "=r"(qraw0) : "l"(qp));
            asm volatile("ld.global.nc.u16 %0, [%1+16];" : "=r"(qraw1) : "l"(qp));
        }
        __nv_bfloat16* optr = out + head * DH + half * 64 + row0 + 8 * (t & 1);
        asm volatile("" : "+l"(optr));

        const uint64_t da0 = make_desc(kvbase), db0 = make_desc(ebase);
        float acc[8];
        float p[4];
        int s = 0, ph = 0;
#pragma unroll 1
        for (int i = 0; i < NT; i++) {
            if (i == TPM + TPM / 2) {
                mbar_wait_cluster(smem_u32(&score_bar), 0);
                const int r = lane & 15;
                float sc = 0.f;
#pragma unroll
                for (int w = 0; w < 8; w++) sc += score_part[w][r];
                sc = rbf(rbf(sc) * 0.08838834764831845f);
                float mx = sc;
#pragma unroll
                for (int o = 8; o >= 1; o >>= 1) mx = fmaxf(mx, __shfl_xor_sync(0xffffffffu, mx, o));
                const float ex = expf(sc - mx);
                float sum = ex;
#pragma unroll
                for (int o = 8; o >= 1; o >>= 1) sum += __shfl_xor_sync(0xffffffffu, sum, o);
                const float pr = rbf(ex / sum);
                p[0] = __shfl_sync(0xffffffffu, pr, 2 * t);
                p[1] = __shfl_sync(0xffffffffu, pr, 2 * t + 1);
                p[2] = __shfl_sync(0xffffffffu, pr, 8 + 2 * t);
                p[3] = __shfl_sync(0xffffffffu, pr, 9 + 2 * t);
            }
            mbar_wait(smem_u32(&full_bar[s]), ph);
            const uint64_t da = da0 + s * (KV_BYTES >> 4), db = db0 + s * (E_BYTES >> 4);
            const int first = (i == 0 || i == TPM) ? 0 : 1;
            reg_fence(acc);
            wgmma_fence();
#pragma unroll
            for (int k = 0; k < TR / 16; k++)
                wgmma_m64n16k16(acc, da + k * (2048 >> 4), db + (k >> 2) * (2048 >> 4) + (k & 3) * (32 >> 4), k == 0 ? first : 1);
            wgmma_commit();
            wgmma_wait0();
            reg_fence(acc);
            if (lane == 0) mbar_arrive(smem_u32(&empty_bar[s]));
            if (i == TPM - 1) {
                float sp[4], q0, q1;
                asm volatile("shl.b32 %0, %1, 16;" : "=f"(q0) : "r"(qraw0));
                asm volatile("shl.b32 %0, %1, 16;" : "=f"(q1) : "r"(qraw1));
                sp[0] = q0 * rbf(acc[0]) + q1 * rbf(acc[2]);
                sp[1] = q0 * rbf(acc[1]) + q1 * rbf(acc[3]);
                sp[2] = q0 * rbf(acc[4]) + q1 * rbf(acc[6]);
                sp[3] = q0 * rbf(acc[5]) + q1 * rbf(acc[7]);
#pragma unroll
                for (int o = 4; o <= 16; o <<= 1)
#pragma unroll
                    for (int c = 0; c < 4; c++) sp[c] += __shfl_xor_sync(0xffffffffu, sp[c], o);
                asm volatile("barrier.cluster.wait.aligned;" ::: "memory");
                if (lane < 4) {
                    const uint32_t a = smem_u32(&score_part[half * 4 + warp][2 * t]);
#pragma unroll
                    for (int rk = 0; rk < 2; rk++) {
                        const uint32_t ra = mapa(a, rk), rb = mapa(smem_u32(&score_bar), rk);
                        asm volatile("st.async.shared::cluster.mbarrier::complete_tx::bytes.v2.f32 [%0], {%1, %2}, [%3];"
                                     ::"r"(ra), "f"(sp[0]), "f"(sp[1]), "r"(rb) : "memory");
                        asm volatile("st.async.shared::cluster.mbarrier::complete_tx::bytes.v2.f32 [%0], {%1, %2}, [%3];"
                                     ::"r"(ra + 32), "f"(sp[2]), "f"(sp[3]), "r"(rb) : "memory");
                    }
                }
            }
            if (++s == NST) { s = 0; ph ^= 1; }
        }
        float x[8];
#pragma unroll
        for (int c = 0; c < 8; c += 2) rbf2(acc[c], acc[c + 1], x[c], x[c + 1]);
        const float o0 = (p[0] * x[0] + p[1] * x[1]) + (p[2] * x[4] + p[3] * x[5]);
        const float o1 = (p[0] * x[2] + p[1] * x[3]) + (p[2] * x[6] + p[3] * x[7]);
        float keep = (t & 1) ? o1 : o0;
        keep += __shfl_xor_sync(0xffffffffu, (t & 1) ? o0 : o1, 1);
        keep += __shfl_xor_sync(0xffffffffu, keep, 2);
        if (t < 2) asm volatile("st.global.b16 [%0], %1;" ::"l"(optr), "h"(__bfloat16_as_ushort(__float2bfloat16_rn(keep))) : "memory");
    }
}

typedef CUresult (*EncodeTiledFn)(CUtensorMap*, CUtensorMapDataType, cuuint32_t, void*, const cuuint64_t*, const cuuint64_t*,
                                  const cuuint32_t*, const cuuint32_t*, CUtensorMapInterleave, CUtensorMapSwizzle,
                                  CUtensorMapL2promotion, CUtensorMapFloatOOBfill);

void encode_kv(EncodeTiledFn enc, CUtensorMap* m, void* p) {
    cuuint64_t dims[2] = {(cuuint64_t)DH, (cuuint64_t)NHEADS * SKV};
    cuuint64_t str[1] = {DH * 2};
    cuuint32_t box[2] = {64, TR};
    cuuint32_t es[2] = {1, 1};
    enc(m, CU_TENSOR_MAP_DATA_TYPE_BFLOAT16, 2, p, dims, str, box, es, CU_TENSOR_MAP_INTERLEAVE_NONE,
        CU_TENSOR_MAP_SWIZZLE_128B, CU_TENSOR_MAP_L2_PROMOTION_L2_256B, CU_TENSOR_MAP_FLOAT_OOB_FILL_NONE);
}
void encode_ef(EncodeTiledFn enc, CUtensorMap* m, void* p) {
    cuuint64_t dims[3] = {64, (cuuint64_t)RK, (cuuint64_t)SKV / 64};
    cuuint64_t str[2] = {SKV * 2, 128};
    cuuint32_t box[3] = {64, RK, TR / 64};
    cuuint32_t es[3] = {1, 1, 1};
    enc(m, CU_TENSOR_MAP_DATA_TYPE_BFLOAT16, 3, p, dims, str, box, es, CU_TENSOR_MAP_INTERLEAVE_NONE,
        CU_TENSOR_MAP_SWIZZLE_128B, CU_TENSOR_MAP_L2_PROMOTION_NONE, CU_TENSOR_MAP_FLOAT_OOB_FILL_NONE);
}

}

extern "C" void kernel_launch(void* const* d_in, const int* in_sizes, int n_in, void* d_out, int out_size) {
    (void)in_sizes; (void)n_in; (void)out_size;
    static EncodeTiledFn enc = nullptr;
    if (!enc) {
        cudaDriverEntryPointQueryResult qr;
        cudaGetDriverEntryPoint("cuTensorMapEncodeTiled", (void**)&enc, cudaEnableDefault, &qr);
        if (!enc) return;
        cudaFuncSetAttribute(linformer_decode_kernel, cudaFuncAttributeMaxDynamicSharedMemorySize, SMEM_BYTES);
    }
    CUtensorMap mK, mV, mE, mF;
    encode_kv(enc, &mK, d_in[1]);
    encode_kv(enc, &mV, d_in[2]);
    encode_ef(enc, &mE, d_in[3]);
    encode_ef(enc, &mF, d_in[4]);
    linformer_decode_kernel<<<2 * NHEADS, NTHREADS, SMEM_BYTES, cudaStreamPerThread>>>(
        (const char*)d_in[1], (const char*)d_in[3], (const char*)d_in[4], mK, mV, mE, mF, (const __nv_bfloat16*)d_in[0], (__nv_bfloat16*)d_out);
}
```
